```python
import torch

def _softmax(x, axis=-1):
    return torch.softmax(x, dim=axis)
def _gelu(x):
    return torch.nn.functional.gelu(x, approximate="tanh")
def _silu(x):
    return torch.nn.functional.silu(x)
def _sigmoid(x):
    return torch.sigmoid(x)
def _layernorm(x, axis=-1, eps=1e-5):
    m = x.mean(dim=axis, keepdim=True)
    v = x.var(dim=axis, keepdim=True, unbiased=False)
    return (x - m) / torch.sqrt(v + eps)
def _scatter_add(tgt, idx, src, axis=0):
    return tgt.clone().index_add_(axis, idx, src)
def _segment_sum(src, seg, n):
    out = torch.zeros((n,) + src.shape[1:], dtype=src.dtype)
    return out.index_add_(0, seg, src)
def _pad(x, pw):
    flat = tuple(v for pair in reversed(pw) for v in pair)
    return torch.nn.functional.pad(x, flat)

kernel_name = 'parallel_sum__sliding_local_dilated__mixer_channel_mlp__prompt'

def setup_inputs():

    _w = (lambda a: (lambda t: t.to(torch.bfloat16) if t.is_floating_point() else t)(torch.as_tensor(a)))
    def _A_setup():
        B, S, D = 1, 2048, 640
        return {
            "x": _w((lambda *s: torch.randn(*s, dtype=torch.bfloat16) * 0.05)(B, S, D)),
            "wqkv": _w((lambda *s: torch.randn(*s, dtype=torch.bfloat16) * 0.05)(D, 3 * D)),
            "wo": _w((lambda *s: torch.randn(*s, dtype=torch.bfloat16) * 0.05)(D, D)),
        }
    _A_in = _A_setup()

    def _B_setup():
        B, S, D, F = 1, 2048, 640, 1728
        return {
            "x": _w((lambda *s: torch.randn(*s, dtype=torch.bfloat16) * 0.05)(B, S, D)),
            "w1": _w((lambda *s: torch.randn(*s, dtype=torch.bfloat16) * 3.2)(D, F) * (D ** -0.5)),
            "b1": _w((lambda *s: torch.randn(*s, dtype=torch.bfloat16) * 1.6)(F)),
            "w2": _w((lambda *s: torch.randn(*s, dtype=torch.bfloat16) * 0.2)(F, D) * (F ** -0.5)),
            "b2": _w((lambda *s: torch.randn(*s, dtype=torch.bfloat16) * 0.4)(D)),
        }
    _B_in = _B_setup()

    return {
        "A_x": _A_in["x"],
        "A_wqkv": _A_in["wqkv"],
        "A_wo": _A_in["wo"],
        "B_x": _B_in["x"],
        "B_w1": _B_in["w1"],
        "B_b1": _B_in["b1"],
        "B_w2": _B_in["w2"],
        "B_b2": _B_in["b2"],
    }

def reference(A_x, A_wqkv, A_wo, B_x, B_w1, B_b1, B_w2, B_b2):
    def _A_ref(x, wqkv, wo):
        B, S, D = x.shape
        H = 32; Dh = D // H
        W, dil = 8, 2
        qkv = (lambda x, *d: x.permute(*d))((x @ wqkv).reshape(B, S, 3, H, Dh), 2, 0, 3, 1, 4)
        q, k, v = qkv[0], qkv[1], qkv[2]
        scale = Dh ** -0.5
        pos = torch.arange(S)
        off = torch.arange(W) * dil
        idx = pos[:, None] - off[None, :]
        mask = idx >= 0
        idx_c = torch.where(mask, idx, 0).reshape(-1)
        kg = k[:, :, idx_c, :].reshape(B, H, S, W, Dh)
        vg = v[:, :, idx_c, :].reshape(B, H, S, W, Dh)
        logits = torch.einsum("bhsd,bhswd->bhsw", q, kg) * scale
        logits = torch.where(mask[None, None, :, :], logits, -1e9)
        attn = _softmax(logits, axis=-1)
        o = torch.einsum("bhsw,bhswd->bhsd", attn, vg)
        return (lambda x, *d: x.permute(*d))(o, 0, 2, 1, 3).reshape(B, S, D) @ wo

    def _B_ref(x, w1, b1, w2, b2):
        y = _layernorm(x, axis=-1)
        h = _gelu(torch.einsum("bsd,df->bsf", y, w1) + b1)
        return torch.einsum("bsf,fd->bsd", h, w2) + b2

    x = A_x
    xn = _layernorm(x, axis=-1)
    return x + _A_ref(xn, A_wqkv, A_wo) + _B_ref(xn, B_w1, B_b1, B_w2, B_b2)
```

```cpp
#include <cuda_runtime.h>
#include <cuda_bf16.h>
#include <cuda.h>
#include <stdint.h>

typedef __nv_bfloat16 bf16;

constexpr int S = 2048, DM = 640, FF = 1728, NQKV = 1920, KACT = FF + DM;
constexpr int NCTA = 128, NGRID = 132;
constexpr int N1 = 216, N2 = 240, N3 = 160;
constexpr int NSIDE = 224;

constexpr int A_SLOT = 16384;
constexpr int B_BLK = 8192;
constexpr int HP = 432;
constexpr int QP = 496;
constexpr int OFF_A = 0;
constexpr int OFF_B = 4 * A_SLOT;
constexpr int OFF_STG = OFF_B + 12 * B_BLK;
constexpr int OFF_BAR = OFF_STG + 128 * QP;
constexpr int OFF_ID = OFF_BAR + 200;
constexpr int OFF_TAG = OFF_BAR + 204;
constexpr int OFF_R1 = OFF_BAR + 208;
constexpr int OFF_MEAN = OFF_R1 + 512;
constexpr int OFF_RH = OFF_MEAN + 512;
constexpr int OFF_CB = OFF_RH + 512;
constexpr int OFF_CS2 = OFF_CB + 1728;
constexpr int OFF_XT = OFF_STG;
constexpr int OFF_B2 = OFF_XT + 20480;
constexpr int OFF_SEND = OFF_STG + 24576;
constexpr int OFF_O = OFF_B + 6 * B_BLK + 32;
constexpr int OFF_HALO = OFF_MEAN;
constexpr int SMEM_BYTES = OFF_CS2 + 960;
static_assert(OFF_HALO + 7 * 320 <= OFF_CS2 + 960 && SMEM_BYTES + 256 <= 232448 && OFF_HALO % 16 == 0, "smem layout");
#define GATE_STEP 6
#define SIDE_DELAY 300
#define CS_FIRST 1
#define PF_W1 0
#define PF_WQ 0
#define PF_DELAY 0
#define PF2_DELAY 2200
#define CS_DELAY 0
#define H_GAP 150

enum {
  BAR_P1_FULL = 0, BAR_P1_EMPTY = 3, BAR_P2_FULL = 6, BAR_P2_EMPTY = 10, BAR_STG_FULL = 14, BAR_STG_FREE = 15,
  BAR_MISC = 16, BAR_PEER_FREE = 17, BAR_PART = 18, BAR_ATT = 19, BAR_XT = 20, BAR_CS = 21, BAR_OFREE = 22, BAR_GATE = 23, BAR_COUNT = 24
};

enum { CNT_EXIT = 0, CNT_START = 32, CNT_H = 64, CNT_O = 64 + 8 * 32, CNT_TOTAL = 64 + 16 * 32 };

__device__ __align__(1024) bf16 g_act[(size_t)S * KACT];
__device__ unsigned long long g_stat[3 * S];
__device__ unsigned long long g_cs[FF + NQKV];
__device__ uint4 g_part[128 * 8 * 160];
__device__ unsigned long long g_pflag[128 * 8];
__device__ unsigned long long g_halo[128 * 560];
__device__ unsigned int g_cnt[CNT_TOTAL];
#define TR(slot) do {} while (0)
constexpr int SMEM_LAUNCH = SMEM_BYTES;

struct Params {
  alignas(64) CUtensorMap tm_x;
  alignas(64) CUtensorMap tm_w1a;
  alignas(64) CUtensorMap tm_w1b;
  alignas(64) CUtensorMap tm_qm;
  alignas(64) CUtensorMap tm_qr;
  alignas(64) CUtensorMap tm_c1;
  alignas(64) CUtensorMap tm_c2;
  alignas(64) CUtensorMap tm_ost;
  alignas(64) CUtensorMap tm_xt;
  alignas(64) CUtensorMap tm_out;
  alignas(64) CUtensorMap tm_act;
  alignas(64) CUtensorMap tm_w2a;
  alignas(64) CUtensorMap tm_w2b;
  alignas(64) CUtensorMap tm_woa;
  alignas(64) CUtensorMap tm_wob;
  const bf16* x; const bf16* w1; const bf16* wqkv; const bf16* w2; const bf16* wo; const bf16* b1; const bf16* b2;
  bf16* out;
};

__device__ __forceinline__ long long gtime() { long long t; asm volatile("mov.u64 %0, %%globaltimer;" : "=l"(t)); return t; }
__device__ __forceinline__ uint32_t gtime_lo() { uint32_t t; asm volatile("mov.u32 %0, %%globaltimer_lo;" : "=r"(t)); return t; }
__device__ __forceinline__ uint32_t smem_u32(const void* p) { return (uint32_t)__cvta_generic_to_shared(p); }
__device__ __forceinline__ void mbar_init(uint32_t bar, uint32_t cnt) { asm volatile("mbarrier.init.shared::cta.b64 [%0], %1;" :: "r"(bar), "r"(cnt) : "memory"); }
__device__ __forceinline__ void mbar_expect_tx(uint32_t bar, uint32_t bytes) { asm volatile("mbarrier.arrive.expect_tx.shared::cta.b64 _, [%0], %1;" :: "r"(bar), "r"(bytes) : "memory"); }
__device__ __forceinline__ void mbar_arrive(uint32_t bar) { asm volatile("mbarrier.arrive.shared::cta.b64 _, [%0];" :: "r"(bar) : "memory"); }
__device__ __forceinline__ uint32_t mapa(uint32_t addr, uint32_t cta) { uint32_t r; asm volatile("mapa.shared::cluster.u32 %0, %1, %2;" : "=r"(r) : "r"(addr), "r"(cta)); return r; }
__device__ __forceinline__ void mbar_arrive_remote(uint32_t remote_bar) { asm volatile("mbarrier.arrive.shared::cluster.b64 _, [%0];" :: "r"(remote_bar) : "memory"); }
__device__ __forceinline__ void mbar_wait(uint32_t bar, uint32_t parity) {
  asm volatile("{\n.reg .pred p, q;\n.reg .u32 n;\nmov.u32 n, 0;\n"
               "MB_LOOP:\nmbarrier.try_wait.parity.shared::cta.b64 p, [%0], %1, 20000;\n@p bra MB_DONE;\n"
               "add.u32 n, n, 1;\nsetp.gt.u32 q, n, 200000;\n@q trap;\nbra MB_LOOP;\nMB_DONE:\n}"
               :: "r"(bar), "r"(parity) : "memory");
}
__device__ __forceinline__ uint32_t ld_acquire(const unsigned int* p) { uint32_t v; asm volatile("ld.acquire.gpu.global.u32 %0, [%1];" : "=r"(v) : "l"(p) : "memory"); return v; }
__device__ __forceinline__ uint32_t ld_relaxed(const unsigned int* p) { uint32_t v; asm volatile("ld.relaxed.gpu.global.u32 %0, [%1];" : "=r"(v) : "l"(p) : "memory"); return v; }
__device__ __forceinline__ void red_release(unsigned int* p) { asm volatile("red.release.gpu.global.add.u32 [%0], 1;" :: "l"(p) : "memory"); }
__device__ __forceinline__ void wait_counter(const unsigned int* ptr, uint32_t target) {
  asm volatile("{\n.reg .pred p, q;\n.reg .u32 n, v;\n.reg .s32 d;\nmov.u32 n, 0;\n"
               "WC_LOOP:\nld.acquire.gpu.global.u32 v, [%0];\nsub.s32 d, v, %1;\nsetp.ge.s32 p, d, 0;\n@p bra WC_DONE;\n"
               "add.u32 n, n, 1;\nsetp.gt.u32 q, n, 4000000;\n@q trap;\nbra WC_LOOP;\nWC_DONE:\n}"
               :: "l"(ptr), "r"(target) : "memory");
}
__device__ __forceinline__ void st_tagged(unsigned long long* ptr, uint32_t v, uint32_t tag) {
  asm volatile("st.relaxed.gpu.global.b64 [%0], %1;" :: "l"(ptr), "l"((unsigned long long)v | ((unsigned long long)tag << 32)) : "memory");
}
__device__ __forceinline__ uint32_t ld_tagged(const unsigned long long* ptr, uint32_t tag) {
  uint32_t v;
  asm volatile("{\n.reg .pred p, q;\n.reg .u32 n, t;\n.reg .b64 w;\nmov.u32 n, 0;\n"
               "LT_LOOP:\nld.relaxed.gpu.global.b64 w, [%1];\nmov.b64 {%0, t}, w;\nsetp.eq.u32 p, t, %2;\n@p bra LT_DONE;\n"
               "nanosleep.u32 400;\nadd.u32 n, n, 1;\nsetp.gt.u32 q, n, 2000000;\n@q trap;\nbra LT_LOOP;\nLT_DONE:\n}"
               : "=r"(v) : "l"(ptr), "r"(tag) : "memory");
  return v;
}
__device__ __forceinline__ uint32_t ld_tagged_fast(const unsigned long long* ptr, uint32_t tag) {
  uint32_t v;
  asm volatile("{\n.reg .pred p, q;\n.reg .u32 n, t;\n.reg .b64 w;\nmov.u32 n, 0;\n"
               "LF_LOOP:\nld.relaxed.gpu.global.b64 w, [%1];\nmov.b64 {%0, t}, w;\nsetp.eq.u32 p, t, %2;\n@p bra LF_DONE;\n"
               "add.u32 n, n, 1;\nsetp.gt.u32 q, n, 4000000;\n@q trap;\nbra LF_LOOP;\nLF_DONE:\n}"
               : "=r"(v) : "l"(ptr), "r"(tag) : "memory");
  return v;
}
__device__ __forceinline__ unsigned long long ld_word(const unsigned long long* ptr) {
  unsigned long long w;
  asm volatile("ld.relaxed.gpu.global.b64 %0, [%1];" : "=l"(w) : "l"(ptr) : "memory");
  return w;
}
__device__ __forceinline__ void bulk_store(void* gptr, uint32_t src, uint32_t bytes) {
  asm volatile("cp.async.bulk.global.shared::cta.bulk_group [%0], [%1], %2;" :: "l"(gptr), "r"(src), "r"(bytes) : "memory");
}
__device__ __forceinline__ uint32_t lds_u32(uint32_t a) { uint32_t v; asm volatile("ld.shared.u32 %0, [%1];" : "=r"(v) : "r"(a)); return v; }
__device__ __forceinline__ void fence_async_smem() { asm volatile("fence.proxy.async.shared::cta;" ::: "memory"); }
__device__ __forceinline__ void fence_async_global() { asm volatile("fence.proxy.async.global;" ::: "memory"); }
__device__ __forceinline__ void named_bar(int id, int n) { asm volatile("bar.sync %0, %1;" :: "r"(id), "r"(n) : "memory"); }
__device__ __forceinline__ void tma_2d(uint32_t dst, const CUtensorMap* tm, int c0, int c1, uint32_t bar) {
  asm volatile("cp.async.bulk.tensor.2d.shared::cluster.global.mbarrier::complete_tx::bytes [%0], [%1, {%3, %4}], [%2];"
    :: "r"(dst), "l"(tm), "r"(bar), "r"(c0), "r"(c1) : "memory");
}
__device__ __forceinline__ void tma_3d(uint32_t dst, const CUtensorMap* tm, int c0, int c1, int c2, uint32_t bar) {
  asm volatile("cp.async.bulk.tensor.3d.shared::cluster.global.mbarrier::complete_tx::bytes [%0], [%1, {%3, %4, %5}], [%2];"
    :: "r"(dst), "l"(tm), "r"(bar), "r"(c0), "r"(c1), "r"(c2) : "memory");
}
__device__ __forceinline__ void tma_3d_mc(uint32_t dst, const CUtensorMap* tm, int c0, int c1, int c2, uint32_t bar) {
  asm volatile("cp.async.bulk.tensor.3d.shared::cluster.global.mbarrier::complete_tx::bytes.multicast::cluster [%0], [%1, {%3, %4, %5}], [%2], %6;"
    :: "r"(dst), "l"(tm), "r"(bar), "r"(c0), "r"(c1), "r"(c2), "h"((uint16_t)3) : "memory");
}
__device__ __forceinline__ void tma_4d_mc(uint32_t dst, const CUtensorMap* tm, int c0, int c1, int c2, int c3, uint32_t bar) {
  asm volatile("cp.async.bulk.tensor.4d.shared::cluster.global.mbarrier::complete_tx::bytes.multicast::cluster [%0], [%1, {%3, %4, %5, %6}], [%2], %7;"
    :: "r"(dst), "l"(tm), "r"(bar), "r"(c0), "r"(c1), "r"(c2), "r"(c3), "h"((uint16_t)3) : "memory");
}
__device__ __forceinline__ void tma_4d(uint32_t dst, const CUtensorMap* tm, int c0, int c1, int c2, int c3, uint32_t bar) {
  asm volatile("cp.async.bulk.tensor.4d.shared::cluster.global.mbarrier::complete_tx::bytes [%0], [%1, {%3, %4, %5, %6}], [%2];"
    :: "r"(dst), "l"(tm), "r"(bar), "r"(c0), "r"(c1), "r"(c2), "r"(c3) : "memory");
}
__device__ __forceinline__ void tma_store_2d(const CUtensorMap* tm, uint32_t src, int c0, int c1) {
  asm volatile("cp.async.bulk.tensor.2d.global.shared::cta.bulk_group [%0, {%2, %3}], [%1];"
    :: "l"(tm), "r"(src), "r"(c0), "r"(c1) : "memory");
}
__device__ __forceinline__ void tma_store_4d(const CUtensorMap* tm, uint32_t src, int c0, int c1, int c2, int c3) {
  asm volatile("cp.async.bulk.tensor.4d.global.shared::cta.bulk_group [%0, {%2, %3, %4, %5}], [%1];"
    :: "l"(tm), "r"(src), "r"(c0), "r"(c1), "r"(c2), "r"(c3) : "memory");
}
__device__ __forceinline__ void bulk_load(uint32_t dst, const void* src, uint32_t bytes, uint32_t bar) {
  asm volatile("cp.async.bulk.shared::cluster.global.mbarrier::complete_tx::bytes [%0], [%1], %2, [%3];"
    :: "r"(dst), "l"(src), "r"(bytes), "r"(bar) : "memory");
}
__device__ __forceinline__ void tma_store_3d(const CUtensorMap* tm, uint32_t src, int c0, int c1, int c2) {
  asm volatile("cp.async.bulk.tensor.3d.global.shared::cta.bulk_group [%0, {%2, %3, %4}], [%1];"
    :: "l"(tm), "r"(src), "r"(c0), "r"(c1), "r"(c2) : "memory");
}
__device__ __forceinline__ void bulk_commit() { asm volatile("cp.async.bulk.commit_group;" ::: "memory"); }
__device__ __forceinline__ void bulk_wait_read() { asm volatile("cp.async.bulk.wait_group.read 0;" ::: "memory"); }
__device__ __forceinline__ void bulk_wait() { asm volatile("cp.async.bulk.wait_group 0;" ::: "memory"); }
__device__ __forceinline__ void l2_prefetch(const void* p, uint32_t bytes) { asm volatile("cp.async.bulk.prefetch.L2.global [%0], %1;" :: "l"(p), "r"(bytes) : "memory"); }
__device__ __forceinline__ void tma_prefetch_3d(const CUtensorMap* tm, int c0, int c1, int c2) {
  asm volatile("cp.async.bulk.prefetch.tensor.3d.L2.global.tile [%0, {%1, %2, %3}];" :: "l"(tm), "r"(c0), "r"(c1), "r"(c2) : "memory");
}
__device__ __forceinline__ void prefetch_l2(const void* p) { asm volatile("prefetch.global.L2 [%0];" :: "l"(p) : "memory"); }
__device__ __forceinline__ void prefetch_tmap(const CUtensorMap* tm) { asm volatile("prefetch.tensormap [%0];" :: "l"(tm) : "memory"); }
__device__ __forceinline__ void wgmma_fence() { asm volatile("wgmma.fence.sync.aligned;" ::: "memory"); }
__device__ __forceinline__ void wgmma_commit() { asm volatile("wgmma.commit_group.sync.aligned;" ::: "memory"); }
template <int N> __device__ __forceinline__ void wgmma_wait() { asm volatile("wgmma.wait_group.sync.aligned %0;" :: "n"(N) : "memory"); }
__device__ __forceinline__ uint32_t desc_lo(uint32_t addr, uint32_t lbo) { return ((addr & 0x3FFFF) >> 4) | ((lbo >> 4) << 16); }
constexpr uint32_t DESC_HI_128 = (1024 >> 4) | (1u << 30), DESC_HI_32 = (256 >> 4) | (3u << 30);
__device__ __forceinline__ uint64_t desc(uint32_t lo, uint32_t hi) { return ((uint64_t)hi << 32) | lo; }
template <int R> __device__ __forceinline__ void reg_alloc() { asm volatile("setmaxnreg.inc.sync.aligned.u32 %0;" :: "n"(R)); }
template <int R> __device__ __forceinline__ void reg_dealloc() { asm volatile("setmaxnreg.dec.sync.aligned.u32 %0;" :: "n"(R)); }
__device__ __forceinline__ uint32_t pack_bf16(float lo, float hi) { uint32_t r; asm("cvt.rn.bf16x2.f32 %0, %1, %2;" : "=r"(r) : "f"(hi), "f"(lo)); return r; }
__device__ __forceinline__ float bf_lo(uint32_t v) { return __uint_as_float(v << 16); }
__device__ __forceinline__ float bf_hi(uint32_t v) { return __uint_as_float(v & 0xffff0000u); }
__device__ __forceinline__ void stsm_x4(uint32_t addr, uint32_t a, uint32_t b, uint32_t c, uint32_t d) {
  asm volatile("stmatrix.sync.aligned.m8n8.x4.shared.b16 [%0], {%1, %2, %3, %4};" :: "r"(addr), "r"(a), "r"(b), "r"(c), "r"(d) : "memory");
}
__device__ __forceinline__ void stsm_x2(uint32_t addr, uint32_t a, uint32_t b) {
  asm volatile("stmatrix.sync.aligned.m8n8.x2.shared.b16 [%0], {%1, %2};" :: "r"(addr), "r"(a), "r"(b) : "memory");
}
__device__ __forceinline__ float2 lds_f2(uint32_t a) { float2 v; asm volatile("ld.shared.v2.f32 {%0, %1}, [%2];" : "=f"(v.x), "=f"(v.y) : "r"(a)); return v; }
__device__ __forceinline__ float lds_f(uint32_t a) { float v; asm volatile("ld.shared.f32 %0, [%1];" : "=f"(v) : "r"(a)); return v; }
__device__ __forceinline__ uint32_t launder(uint32_t a) { asm volatile("" : "+r"(a) :: "memory"); return a; }
__device__ __forceinline__ float2 lds_f2_nv(uint32_t a) { float2 v; asm("ld.shared.v2.f32 {%0, %1}, [%2];" : "=f"(v.x), "=f"(v.y) : "r"(a)); return v; }
__device__ __forceinline__ float4 lds_f4_nv(uint32_t a) { float4 v; asm("ld.shared.v4.f32 {%0, %1, %2, %3}, [%4];" : "=f"(v.x), "=f"(v.y), "=f"(v.z), "=f"(v.w) : "r"(a)); return v; }
__device__ __forceinline__ float lds_f_nv(uint32_t a) { float v; asm("ld.shared.f32 %0, [%1];" : "=f"(v) : "r"(a)); return v; }
__device__ __forceinline__ void sts_f(uint32_t a, float v) { asm volatile("st.shared.f32 [%0], %1;" :: "r"(a), "f"(v) : "memory"); }
__device__ __forceinline__ uint4 lds_u4(uint32_t a) { uint4 v; asm volatile("ld.shared.v4.u32 {%0, %1, %2, %3}, [%4];" : "=r"(v.x), "=r"(v.y), "=r"(v.z), "=r"(v.w) : "r"(a)); return v; }
__device__ __forceinline__ float4 lds_f4(uint32_t a) { float4 v; asm volatile("ld.shared.v4.f32 {%0, %1, %2, %3}, [%4];" : "=f"(v.x), "=f"(v.y), "=f"(v.z), "=f"(v.w) : "r"(a)); return v; }
__device__ __forceinline__ uint2 lds_u2(uint32_t a) { uint2 v; asm volatile("ld.shared.v2.u32 {%0, %1}, [%2];" : "=r"(v.x), "=r"(v.y) : "r"(a)); return v; }
__device__ __forceinline__ void sts_u4(uint32_t a, uint4 v) { asm volatile("st.shared.v4.u32 [%0], {%1, %2, %3, %4};" :: "r"(a), "r"(v.x), "r"(v.y), "r"(v.z), "r"(v.w) : "memory"); }
__device__ __forceinline__ void sts_u32(uint32_t a, uint32_t v) { asm volatile("st.shared.u32 [%0], %1;" :: "r"(a), "r"(v) : "memory"); }
__device__ __forceinline__ void sts_u16(uint32_t a, uint16_t v) { asm volatile("st.shared.u16 [%0], %1;" :: "r"(a), "h"(v) : "memory"); }
__device__ __forceinline__ uint32_t lds_u16(uint32_t a) { uint16_t v; asm volatile("ld.shared.u16 %0, [%1];" : "=h"(v) : "r"(a)); return v; }
__device__ __forceinline__ void cp_async16(uint32_t dst, const void* src) {
  asm volatile("cp.async.cg.shared.global [%0], [%1], 16;" :: "r"(dst), "l"(src) : "memory");
}
__device__ __forceinline__ void named_arrive(int id, int n) { asm volatile("bar.arrive %0, %1;" :: "r"(id), "r"(n) : "memory"); }
__device__ __forceinline__ void sts_f4(uint32_t a, float x, float y, float z, float w) {
  asm volatile("st.shared.v4.f32 [%0], {%1, %2, %3, %4};" :: "r"(a), "f"(x), "f"(y), "f"(z), "f"(w) : "memory");
}
__device__ __forceinline__ void bulk_copy_to_peer(uint32_t rdst, uint32_t src, uint32_t bytes, uint32_t rbar) {
  asm volatile("cp.async.bulk.shared::cluster.shared::cta.mbarrier::complete_tx::bytes [%0], [%1], %2, [%3];"
    :: "r"(rdst), "r"(src), "r"(bytes), "r"(rbar) : "memory");
}
template <int N> __device__ __forceinline__ void acc_fence(float (&acc)[N]) {
#pragma unroll
  for (int i = 0; i < N; i++) asm volatile("" : "+f"(acc[i]) :: "memory");
}
__device__ __forceinline__ void st_cluster_f4(uint32_t raddr, float a, float b, float c, float d) {
  asm volatile("st.shared::cluster.v4.f32 [%0], {%1, %2, %3, %4};" :: "r"(raddr), "f"(a), "f"(b), "f"(c), "f"(d) : "memory");
}
__device__ __forceinline__ void ldsm_x4(uint32_t a, uint32_t& r0, uint32_t& r1, uint32_t& r2, uint32_t& r3) {
  asm volatile("ldmatrix.sync.aligned.m8n8.x4.shared.b16 {%0, %1, %2, %3}, [%4];" : "=r"(r0), "=r"(r1), "=r"(r2), "=r"(r3) : "r"(a));
}
__device__ __forceinline__ void ldsm_x2(uint32_t a, uint32_t& r0, uint32_t& r1) {
  asm volatile("ldmatrix.sync.aligned.m8n8.x2.shared.b16 {%0, %1}, [%2];" : "=r"(r0), "=r"(r1) : "r"(a));
}
__device__ __forceinline__ void ldsm_x1(uint32_t a, uint32_t& r0) {
  asm volatile("ldmatrix.sync.aligned.m8n8.x1.shared.b16 {%0}, [%1];" : "=r"(r0) : "r"(a));
}
__device__ __forceinline__ void ldsm_x4_t(uint32_t a, uint32_t& r0, uint32_t& r1, uint32_t& r2, uint32_t& r3) {
  asm volatile("ldmatrix.sync.aligned.m8n8.x4.trans.shared.b16 {%0, %1, %2, %3}, [%4];" : "=r"(r0), "=r"(r1), "=r"(r2), "=r"(r3) : "r"(a));
}
__device__ __forceinline__ void ldsm_x1_t(uint32_t a, uint32_t& r0) {
  asm volatile("ldmatrix.sync.aligned.m8n8.x1.trans.shared.b16 {%0}, [%1];" : "=r"(r0) : "r"(a));
}
__device__ __forceinline__ void mma_k16(float (&c)[4], uint32_t a0, uint32_t a1, uint32_t a2, uint32_t a3, uint32_t b0, uint32_t b1) {
  asm("mma.sync.aligned.m16n8k16.row.col.f32.bf16.bf16.f32 {%0, %1, %2, %3}, {%4, %5, %6, %7}, {%8, %9}, {%0, %1, %2, %3};"
      : "+f"(c[0]), "+f"(c[1]), "+f"(c[2]), "+f"(c[3]) : "r"(a0), "r"(a1), "r"(a2), "r"(a3), "r"(b0), "r"(b1));
}
__device__ __forceinline__ void mma_k8(float (&c)[4], uint32_t a0, uint32_t a1, uint32_t b0) {
  asm("mma.sync.aligned.m16n8k8.row.col.f32.bf16.bf16.f32 {%0, %1, %2, %3}, {%4, %5}, {%6}, {%0, %1, %2, %3};"
      : "+f"(c[0]), "+f"(c[1]), "+f"(c[2]), "+f"(c[3]) : "r"(a0), "r"(a1), "r"(b0));
}
__device__ __forceinline__ float tanh_fast(float x) { float y; asm("tanh.approx.f32 %0, %1;" : "=f"(y) : "f"(x)); return y; }
__device__ __forceinline__ float rcp_fast(float x) { float y; asm("rcp.approx.ftz.f32 %0, %1;" : "=f"(y) : "f"(x)); return y; }
__device__ __forceinline__ float ex2(float x) { float y; asm("ex2.approx.ftz.f32 %0, %1;" : "=f"(y) : "f"(x)); return y; }
__device__ __forceinline__ float warp_sum(float v) {
#pragma unroll
  for (int o = 16; o > 0; o >>= 1) v += __shfl_xor_sync(0xffffffffu, v, o);
  return v;
}
__device__ __forceinline__ float gelu_half(float hv) {
  const float t = fmaf(hv * hv, 8.f * 0.0356774081f, 2.f * 0.7978845608f);
  return fmaf(hv, tanh_fast(hv * t), hv);
}

__device__ __forceinline__ void cluster_arrive_relaxed() { asm volatile("barrier.cluster.arrive.relaxed.aligned;" ::: "memory"); }
__device__ __forceinline__ void cluster_wait() { asm volatile("barrier.cluster.wait.acquire.aligned;" ::: "memory"); }

template <int OFF, int TOT> __device__ __forceinline__ void wgmma_n128(float (&d)[TOT], uint64_t da, uint64_t db, int sd) {
  asm volatile("{\n.reg .pred p;\nsetp.ne.b32 p, %66, 0;\n"
    "wgmma.mma_async.sync.aligned.m64n128k16.f32.bf16.bf16 "
    "{%0, %1, %2, %3, %4, %5, %6, %7, %8, %9, %10, %11, %12, %13, %14, %15, "
    "%16, %17, %18, %19, %20, %21, %22, %23, %24, %25, %26, %27, %28, %29, %30, %31, "
    "%32, %33, %34, %35, %36, %37, %38, %39, %40, %41, %42, %43, %44, %45, %46, %47, "
    "%48, %49, %50, %51, %52, %53, %54, %55, %56, %57, %58, %59, %60, %61, %62, %63}, "
    "%64, %65, p, 1, 1, 0, 1;\n}\n"
    : "+f"(d[OFF + 0]), "+f"(d[OFF + 1]), "+f"(d[OFF + 2]), "+f"(d[OFF + 3]), "+f"(d[OFF + 4]), "+f"(d[OFF + 5]), "+f"(d[OFF + 6]), "+f"(d[OFF + 7]),
      "+f"(d[OFF + 8]), "+f"(d[OFF + 9]), "+f"(d[OFF + 10]), "+f"(d[OFF + 11]), "+f"(d[OFF + 12]), "+f"(d[OFF + 13]), "+f"(d[OFF + 14]), "+f"(d[OFF + 15]),
      "+f"(d[OFF + 16]), "+f"(d[OFF + 17]), "+f"(d[OFF + 18]), "+f"(d[OFF + 19]), "+f"(d[OFF + 20]), "+f"(d[OFF + 21]), "+f"(d[OFF + 22]), "+f"(d[OFF + 23]),
      "+f"(d[OFF + 24]), "+f"(d[OFF + 25]), "+f"(d[OFF + 26]), "+f"(d[OFF + 27]), "+f"(d[OFF + 28]), "+f"(d[OFF + 29]), "+f"(d[OFF + 30]), "+f"(d[OFF + 31]),
      "+f"(d[OFF + 32]), "+f"(d[OFF + 33]), "+f"(d[OFF + 34]), "+f"(d[OFF + 35]), "+f"(d[OFF + 36]), "+f"(d[OFF + 37]), "+f"(d[OFF + 38]), "+f"(d[OFF + 39]),
      "+f"(d[OFF + 40]), "+f"(d[OFF + 41]), "+f"(d[OFF + 42]), "+f"(d[OFF + 43]), "+f"(d[OFF + 44]), "+f"(d[OFF + 45]), "+f"(d[OFF + 46]), "+f"(d[OFF + 47]),
      "+f"(d[OFF + 48]), "+f"(d[OFF + 49]), "+f"(d[OFF + 50]), "+f"(d[OFF + 51]), "+f"(d[OFF + 52]), "+f"(d[OFF + 53]), "+f"(d[OFF + 54]), "+f"(d[OFF + 55]),
      "+f"(d[OFF + 56]), "+f"(d[OFF + 57]), "+f"(d[OFF + 58]), "+f"(d[OFF + 59]), "+f"(d[OFF + 60]), "+f"(d[OFF + 61]), "+f"(d[OFF + 62]), "+f"(d[OFF + 63])
    : "l"(da), "l"(db), "r"(sd));
}
template <int OFF, int TOT> __device__ __forceinline__ void wgmma_n88(float (&d)[TOT], uint64_t da, uint64_t db, int sd) {
  asm volatile("{\n.reg .pred p;\nsetp.ne.b32 p, %46, 0;\n"
    "wgmma.mma_async.sync.aligned.m64n88k16.f32.bf16.bf16 "
    "{%0, %1, %2, %3, %4, %5, %6, %7, %8, %9, %10, %11, %12, %13, %14, %15, "
    "%16, %17, %18, %19, %20, %21, %22, %23, %24, %25, %26, %27, %28, %29, %30, %31, "
    "%32, %33, %34, %35, %36, %37, %38, %39, %40, %41, %42, %43}, "
    "%44, %45, p, 1, 1, 0, 1;\n}\n"
    : "+f"(d[OFF + 0]), "+f"(d[OFF + 1]), "+f"(d[OFF + 2]), "+f"(d[OFF + 3]), "+f"(d[OFF + 4]), "+f"(d[OFF + 5]), "+f"(d[OFF + 6]), "+f"(d[OFF + 7]),
      "+f"(d[OFF + 8]), "+f"(d[OFF + 9]), "+f"(d[OFF + 10]), "+f"(d[OFF + 11]), "+f"(d[OFF + 12]), "+f"(d[OFF + 13]), "+f"(d[OFF + 14]), "+f"(d[OFF + 15]),
      "+f"(d[OFF + 16]), "+f"(d[OFF + 17]), "+f"(d[OFF + 18]), "+f"(d[OFF + 19]), "+f"(d[OFF + 20]), "+f"(d[OFF + 21]), "+f"(d[OFF + 22]), "+f"(d[OFF + 23]),
      "+f"(d[OFF + 24]), "+f"(d[OFF + 25]), "+f"(d[OFF + 26]), "+f"(d[OFF + 27]), "+f"(d[OFF + 28]), "+f"(d[OFF + 29]), "+f"(d[OFF + 30]), "+f"(d[OFF + 31]),
      "+f"(d[OFF + 32]), "+f"(d[OFF + 33]), "+f"(d[OFF + 34]), "+f"(d[OFF + 35]), "+f"(d[OFF + 36]), "+f"(d[OFF + 37]), "+f"(d[OFF + 38]), "+f"(d[OFF + 39]),
      "+f"(d[OFF + 40]), "+f"(d[OFF + 41]), "+f"(d[OFF + 42]), "+f"(d[OFF + 43])
    : "l"(da), "l"(db), "r"(sd));
}
template <int OFF, int TOT> __device__ __forceinline__ void wgmma_n192(float (&d)[TOT], uint64_t da, uint64_t db, int sd) {
  asm volatile("{\n.reg .pred p;\nsetp.ne.b32 p, %98, 0;\n"
    "wgmma.mma_async.sync.aligned.m64n192k16.f32.bf16.bf16 "
    "{%0, %1, %2, %3, %4, %5, %6, %7, %8, %9, %10, %11, %12, %13, %14, %15, "
    "%16, %17, %18, %19, %20, %21, %22, %23, %24, %25, %26, %27, %28, %29, %30, %31, "
    "%32, %33, %34, %35, %36, %37, %38, %39, %40, %41, %42, %43, %44, %45, %46, %47, "
    "%48, %49, %50, %51, %52, %53, %54, %55, %56, %57, %58, %59, %60, %61, %62, %63, "
    "%64, %65, %66, %67, %68, %69, %70, %71, %72, %73, %74, %75, %76, %77, %78, %79, "
    "%80, %81, %82, %83, %84, %85, %86, %87, %88, %89, %90, %91, %92, %93, %94, %95}, "
    "%96, %97, p, 1, 1, 0, 1;\n}\n"
    : "+f"(d[OFF + 0]), "+f"(d[OFF + 1]), "+f"(d[OFF + 2]), "+f"(d[OFF + 3]), "+f"(d[OFF + 4]), "+f"(d[OFF + 5]), "+f"(d[OFF + 6]), "+f"(d[OFF + 7]),
      "+f"(d[OFF + 8]), "+f"(d[OFF + 9]), "+f"(d[OFF + 10]), "+f"(d[OFF + 11]), "+f"(d[OFF + 12]), "+f"(d[OFF + 13]), "+f"(d[OFF + 14]), "+f"(d[OFF + 15]),
      "+f"(d[OFF + 16]), "+f"(d[OFF + 17]), "+f"(d[OFF + 18]), "+f"(d[OFF + 19]), "+f"(d[OFF + 20]), "+f"(d[OFF + 21]), "+f"(d[OFF + 22]), "+f"(d[OFF + 23]),
      "+f"(d[OFF + 24]), "+f"(d[OFF + 25]), "+f"(d[OFF + 26]), "+f"(d[OFF + 27]), "+f"(d[OFF + 28]), "+f"(d[OFF + 29]), "+f"(d[OFF + 30]), "+f"(d[OFF + 31]),
      "+f"(d[OFF + 32]), "+f"(d[OFF + 33]), "+f"(d[OFF + 34]), "+f"(d[OFF + 35]), "+f"(d[OFF + 36]), "+f"(d[OFF + 37]), "+f"(d[OFF + 38]), "+f"(d[OFF + 39]),
      "+f"(d[OFF + 40]), "+f"(d[OFF + 41]), "+f"(d[OFF + 42]), "+f"(d[OFF + 43]), "+f"(d[OFF + 44]), "+f"(d[OFF + 45]), "+f"(d[OFF + 46]), "+f"(d[OFF + 47]),
      "+f"(d[OFF + 48]), "+f"(d[OFF + 49]), "+f"(d[OFF + 50]), "+f"(d[OFF + 51]), "+f"(d[OFF + 52]), "+f"(d[OFF + 53]), "+f"(d[OFF + 54]), "+f"(d[OFF + 55]),
      "+f"(d[OFF + 56]), "+f"(d[OFF + 57]), "+f"(d[OFF + 58]), "+f"(d[OFF + 59]), "+f"(d[OFF + 60]), "+f"(d[OFF + 61]), "+f"(d[OFF + 62]), "+f"(d[OFF + 63]),
      "+f"(d[OFF + 64]), "+f"(d[OFF + 65]), "+f"(d[OFF + 66]), "+f"(d[OFF + 67]), "+f"(d[OFF + 68]), "+f"(d[OFF + 69]), "+f"(d[OFF + 70]), "+f"(d[OFF + 71]),
      "+f"(d[OFF + 72]), "+f"(d[OFF + 73]), "+f"(d[OFF + 74]), "+f"(d[OFF + 75]), "+f"(d[OFF + 76]), "+f"(d[OFF + 77]), "+f"(d[OFF + 78]), "+f"(d[OFF + 79]),
      "+f"(d[OFF + 80]), "+f"(d[OFF + 81]), "+f"(d[OFF + 82]), "+f"(d[OFF + 83]), "+f"(d[OFF + 84]), "+f"(d[OFF + 85]), "+f"(d[OFF + 86]), "+f"(d[OFF + 87]),
      "+f"(d[OFF + 88]), "+f"(d[OFF + 89]), "+f"(d[OFF + 90]), "+f"(d[OFF + 91]), "+f"(d[OFF + 92]), "+f"(d[OFF + 93]), "+f"(d[OFF + 94]), "+f"(d[OFF + 95])
    : "l"(da), "l"(db), "r"(sd));
}
template <int OFF, int TOT> __device__ __forceinline__ void wgmma_n48(float (&d)[TOT], uint64_t da, uint64_t db, int sd) {
  asm volatile("{\n.reg .pred p;\nsetp.ne.b32 p, %26, 0;\n"
    "wgmma.mma_async.sync.aligned.m64n48k16.f32.bf16.bf16 "
    "{%0, %1, %2, %3, %4, %5, %6, %7, %8, %9, %10, %11, %12, %13, %14, %15, "
    "%16, %17, %18, %19, %20, %21, %22, %23}, "
    "%24, %25, p, 1, 1, 0, 1;\n}\n"
    : "+f"(d[OFF + 0]), "+f"(d[OFF + 1]), "+f"(d[OFF + 2]), "+f"(d[OFF + 3]), "+f"(d[OFF + 4]), "+f"(d[OFF + 5]), "+f"(d[OFF + 6]), "+f"(d[OFF + 7]),
      "+f"(d[OFF + 8]), "+f"(d[OFF + 9]), "+f"(d[OFF + 10]), "+f"(d[OFF + 11]), "+f"(d[OFF + 12]), "+f"(d[OFF + 13]), "+f"(d[OFF + 14]), "+f"(d[OFF + 15]),
      "+f"(d[OFF + 16]), "+f"(d[OFF + 17]), "+f"(d[OFF + 18]), "+f"(d[OFF + 19]), "+f"(d[OFF + 20]), "+f"(d[OFF + 21]), "+f"(d[OFF + 22]), "+f"(d[OFF + 23])
    : "l"(da), "l"(db), "r"(sd));
}
template <int OFF, int TOT> __device__ __forceinline__ void wgmma_n160(float (&d)[TOT], uint64_t da, uint64_t db, int sd) {
  asm volatile("{\n.reg .pred p;\nsetp.ne.b32 p, %82, 0;\n"
    "wgmma.mma_async.sync.aligned.m64n160k16.f32.bf16.bf16 "
    "{%0, %1, %2, %3, %4, %5, %6, %7, %8, %9, %10, %11, %12, %13, %14, %15, "
    "%16, %17, %18, %19, %20, %21, %22, %23, %24, %25, %26, %27, %28, %29, %30, %31, "
    "%32, %33, %34, %35, %36, %37, %38, %39, %40, %41, %42, %43, %44, %45, %46, %47, "
    "%48, %49, %50, %51, %52, %53, %54, %55, %56, %57, %58, %59, %60, %61, %62, %63, "
    "%64, %65, %66, %67, %68, %69, %70, %71, %72, %73, %74, %75, %76, %77, %78, %79}, "
    "%80, %81, p, 1, 1, 0, 1;\n}\n"
    : "+f"(d[OFF + 0]), "+f"(d[OFF + 1]), "+f"(d[OFF + 2]), "+f"(d[OFF + 3]), "+f"(d[OFF + 4]), "+f"(d[OFF + 5]), "+f"(d[OFF + 6]), "+f"(d[OFF + 7]),
      "+f"(d[OFF + 8]), "+f"(d[OFF + 9]), "+f"(d[OFF + 10]), "+f"(d[OFF + 11]), "+f"(d[OFF + 12]), "+f"(d[OFF + 13]), "+f"(d[OFF + 14]), "+f"(d[OFF + 15]),
      "+f"(d[OFF + 16]), "+f"(d[OFF + 17]), "+f"(d[OFF + 18]), "+f"(d[OFF + 19]), "+f"(d[OFF + 20]), "+f"(d[OFF + 21]), "+f"(d[OFF + 22]), "+f"(d[OFF + 23]),
      "+f"(d[OFF + 24]), "+f"(d[OFF + 25]), "+f"(d[OFF + 26]), "+f"(d[OFF + 27]), "+f"(d[OFF + 28]), "+f"(d[OFF + 29]), "+f"(d[OFF + 30]), "+f"(d[OFF + 31]),
      "+f"(d[OFF + 32]), "+f"(d[OFF + 33]), "+f"(d[OFF + 34]), "+f"(d[OFF + 35]), "+f"(d[OFF + 36]), "+f"(d[OFF + 37]), "+f"(d[OFF + 38]), "+f"(d[OFF + 39]),
      "+f"(d[OFF + 40]), "+f"(d[OFF + 41]), "+f"(d[OFF + 42]), "+f"(d[OFF + 43]), "+f"(d[OFF + 44]), "+f"(d[OFF + 45]), "+f"(d[OFF + 46]), "+f"(d[OFF + 47]),
      "+f"(d[OFF + 48]), "+f"(d[OFF + 49]), "+f"(d[OFF + 50]), "+f"(d[OFF + 51]), "+f"(d[OFF + 52]), "+f"(d[OFF + 53]), "+f"(d[OFF + 54]), "+f"(d[OFF + 55]),
      "+f"(d[OFF + 56]), "+f"(d[OFF + 57]), "+f"(d[OFF + 58]), "+f"(d[OFF + 59]), "+f"(d[OFF + 60]), "+f"(d[OFF + 61]), "+f"(d[OFF + 62]), "+f"(d[OFF + 63]),
      "+f"(d[OFF + 64]), "+f"(d[OFF + 65]), "+f"(d[OFF + 66]), "+f"(d[OFF + 67]), "+f"(d[OFF + 68]), "+f"(d[OFF + 69]), "+f"(d[OFF + 70]), "+f"(d[OFF + 71]),
      "+f"(d[OFF + 72]), "+f"(d[OFF + 73]), "+f"(d[OFF + 74]), "+f"(d[OFF + 75]), "+f"(d[OFF + 76]), "+f"(d[OFF + 77]), "+f"(d[OFF + 78]), "+f"(d[OFF + 79])
    : "l"(da), "l"(db), "r"(sd));
}

template <int N> __device__ __forceinline__ void mma_step(float (&acc)[N / 2], uint32_t a_lo, uint32_t b_lo,
                                                          int accumulate, bool release, uint32_t release_bar, uint32_t release_peer, int lane) {
  wgmma_fence();
#pragma unroll
  for (int kk = 0; kk < 4; kk++) {
    const uint64_t da = desc(a_lo + kk * 2, DESC_HI_128);
    const int sd = kk == 0 ? accumulate : 1;
    if constexpr (N == N3) {
      wgmma_n160<0>(acc, da, desc(b_lo + (((kk >> 1) * 12288 + (kk & 1) * 2048) >> 4), DESC_HI_128), sd);
    } else {
      const uint32_t bk = b_lo + (((kk >> 1) * 16384 + (kk & 1) * 2048) >> 4);
      if constexpr (N == N1) {
        wgmma_n128<0>(acc, da, desc(bk, DESC_HI_128), sd);
        wgmma_n88<64>(acc, da, desc(bk + (8192 >> 4), DESC_HI_128), sd);
      } else {
        const uint32_t br = b_lo + (((kk >> 1) * 16384 + 12288 + (kk & 1) * 512) >> 4) - ((4096 >> 4) << 16) + ((1024 >> 4) << 16);
        wgmma_n192<0>(acc, da, desc(bk, DESC_HI_128), sd);
        wgmma_n48<96>(acc, da, desc(br, DESC_HI_32), sd);
      }
    }
    if (kk == 0) {
      wgmma_commit();
      wgmma_wait<1>();
      if (release && lane == 0) { mbar_arrive(release_bar); mbar_arrive_remote(release_peer); }
    }
  }
  wgmma_commit();
}

template <int N> __device__ __forceinline__ void mainloop1(float (&acc)[N / 2], uint32_t base, int g0, int rank, int wg, int lane, int trace_id) {
  const uint32_t bars = base + OFF_BAR;
  const uint32_t peer_empty = mapa(bars + 8 * BAR_P1_EMPTY, 1 - rank);
  const uint32_t a_lo = desc_lo(base + OFF_A + wg * 8192, 16), b_lo = desc_lo(base + OFF_B, 4096);
  int s = g0 % 3, ph = (g0 / 3) & 1, prev = 0;
#pragma unroll 1
  for (int k = 0; k < 10; k++) {
    mbar_wait(bars + 8 * (BAR_P1_FULL + s), ph);
    if (threadIdx.x == 0) TR(32 + g0 + k);
    if (N == N1 && k == GATE_STEP && threadIdx.x == 0) mbar_arrive(bars + 8 * BAR_GATE);
    mma_step<N>(acc, a_lo + s * (A_SLOT >> 4), b_lo + s * (4 * B_BLK >> 4), k > 0, k > 0,
                bars + 8 * (BAR_P1_EMPTY + prev), peer_empty + 8 * prev, lane);
    prev = s;
    if (++s == 3) { s = 0; ph ^= 1; }
  }
  wgmma_wait<0>();
  acc_fence(acc);
  if (lane == 0) { mbar_arrive(bars + 8 * (BAR_P1_EMPTY + prev)); mbar_arrive_remote(peer_empty + 8 * prev); }
}

__device__ __forceinline__ void gelu_epilogue(const float (&acc)[N1 / 2], uint32_t base, int wg, int warp, int lane) {
  const int row0 = wg * 64 + warp * 16;
  const float r0 = lds_f(base + OFF_RH + 4 * (row0 + (lane >> 2))), r1 = lds_f(base + OFF_RH + 4 * (row0 + 8 + (lane >> 2)));
  const float m0 = -r0 * lds_f(base + OFF_MEAN + 4 * (row0 + (lane >> 2)));
  const float m1 = -r1 * lds_f(base + OFF_MEAN + 4 * (row0 + 8 + (lane >> 2)));
  const uint32_t cba = base + OFF_CB + 16 * (lane & 3);
  const int mi = lane >> 3;
  const uint32_t dst = base + OFF_STG + (row0 + (mi & 1) * 8 + (lane & 7)) * HP + (mi >> 1) * 16;
  float4 c[2][2];
  c[0][0] = lds_f4(cba); c[0][1] = lds_f4(cba + 64);
#pragma unroll
  for (int jp = 0; jp < 14; jp++) {
    const int cur = jp & 1;
    if (jp < 13) { c[cur ^ 1][0] = lds_f4(cba + 128 * (jp + 1)); if (jp < 12 || true) { if (2 * (jp + 1) + 1 < 27) c[cur ^ 1][1] = lds_f4(cba + 128 * (jp + 1) + 64); } }
    uint32_t pk[4];
#pragma unroll
    for (int h = 0; h < 2; h++) {
      const int j = 2 * jp + h;
      if (j < 27) {
        const float4 cc = c[cur][h];
        const float v0 = gelu_half(fmaf(acc[4 * j + 0], r0, fmaf(m0, cc.x, cc.z))), v1 = gelu_half(fmaf(acc[4 * j + 1], r0, fmaf(m0, cc.y, cc.w)));
        const float v2 = gelu_half(fmaf(acc[4 * j + 2], r1, fmaf(m1, cc.x, cc.z))), v3 = gelu_half(fmaf(acc[4 * j + 3], r1, fmaf(m1, cc.y, cc.w)));
        pk[2 * h] = pack_bf16(v0, v1);
        pk[2 * h + 1] = pack_bf16(v2, v3);
      }
    }
    if (jp < 13) stsm_x4(dst + 32 * jp, pk[0], pk[1], pk[2], pk[3]);
    else stsm_x2(dst - (mi >> 1) * 16 + 32 * jp, pk[0], pk[1]);
  }
}

__device__ __forceinline__ void dump_qkv(const float (&acc)[N2 / 2], uint32_t base_in, int wg, int warp, int lane) {
  const uint32_t base = launder(base_in);
  const int row0 = wg * 64 + warp * 16;
  const float m0 = lds_f_nv(base + OFF_MEAN + 4 * (row0 + (lane >> 2)));
  const float m1 = lds_f_nv(base + OFF_MEAN + 4 * (row0 + 8 + (lane >> 2)));
  const uint32_t csa = base + OFF_CS2 + 8 * (lane & 3);
  const int mi = lane >> 3;
  const uint32_t dst = base + OFF_STG + (row0 + (mi & 1) * 8 + (lane & 7)) * QP + (mi >> 1) * 16;
#pragma unroll
  for (int j = 0; j < 30; j += 2) {
    const int off = j < 24 ? (j >> 3) * 160 + (j & 7) * 16 : ((j - 24) >> 1) * 160 + 128;
    const float2 c0 = lds_f2_nv(csa + 32 * j), c1 = lds_f2_nv(csa + 32 * (j + 1));
    stsm_x4(dst + off,
            pack_bf16(fmaf(-m0, c0.x, acc[4 * j + 0]), fmaf(-m0, c0.y, acc[4 * j + 1])),
            pack_bf16(fmaf(-m1, c0.x, acc[4 * j + 2]), fmaf(-m1, c0.y, acc[4 * j + 3])),
            pack_bf16(fmaf(-m0, c1.x, acc[4 * j + 4]), fmaf(-m0, c1.y, acc[4 * j + 5])),
            pack_bf16(fmaf(-m1, c1.x, acc[4 * j + 6]), fmaf(-m1, c1.y, acc[4 * j + 7])));
  }
}

template <int KS> __device__ __forceinline__ void final_epilogue(const float (&acc)[80], const Params& p, uint32_t base, int b, int mt, int nt,
                                                                 int wg, int warp, int lane, int trace_id) {
  constexpr int KEEP = KS * 40, SEND = (1 - KS) * 40;
  const uint32_t bars = base + OFF_BAR;
  const int w8 = wg * 4 + warp;
  const uint32_t tag = lds_u32(base + OFF_TAG);
  const uint32_t sendbuf = base + OFF_SEND + w8 * 2560;
  mbar_wait(bars + 8 * BAR_XT, 0);
#pragma unroll
  for (int j = 0; j < 5; j++) {
    uint4 u;
    u.x = pack_bf16(acc[SEND + 8 * j], acc[SEND + 8 * j + 1]); u.y = pack_bf16(acc[SEND + 8 * j + 2], acc[SEND + 8 * j + 3]);
    u.z = pack_bf16(acc[SEND + 8 * j + 4], acc[SEND + 8 * j + 5]); u.w = pack_bf16(acc[SEND + 8 * j + 6], acc[SEND + 8 * j + 7]);
    sts_u4(sendbuf + j * 512 + lane * 16, u);
  }
  fence_async_smem();
  __syncwarp();
  if (lane == 0) { bulk_store(g_part + (b * 8 + w8) * 160, sendbuf, 2560); bulk_commit(); }
  __syncwarp();
  cluster_arrive_relaxed();
  const int mi = lane >> 3;
  const uint32_t panel = (w8 * 16 + (mi & 1) * 8 + (lane & 7)) * 32 + (mi >> 1) * 16;
  const uint32_t ba = base + OFF_B2 + 8 * (lane & 3);
  float v[40];
#pragma unroll
  for (int j = 0; j < 5; j++) {
    uint32_t x0, x1, x2, x3;
    ldsm_x4(base + OFF_XT + j * 4096 + panel, x0, x1, x2, x3);
    const float2 b0 = lds_f2(ba + 64 * j), b1 = lds_f2(ba + 64 * j + 32);
    v[8 * j] = acc[KEEP + 8 * j] + b0.x + bf_lo(x0); v[8 * j + 1] = acc[KEEP + 8 * j + 1] + b0.y + bf_hi(x0);
    v[8 * j + 2] = acc[KEEP + 8 * j + 2] + b0.x + bf_lo(x1); v[8 * j + 3] = acc[KEEP + 8 * j + 3] + b0.y + bf_hi(x1);
    v[8 * j + 4] = acc[KEEP + 8 * j + 4] + b1.x + bf_lo(x2); v[8 * j + 5] = acc[KEEP + 8 * j + 5] + b1.y + bf_hi(x2);
    v[8 * j + 6] = acc[KEEP + 8 * j + 6] + b1.x + bf_lo(x3); v[8 * j + 7] = acc[KEEP + 8 * j + 7] + b1.y + bf_hi(x3);
  }
  if (lane == 0) {
    bulk_wait();
    st_tagged(&g_pflag[b * 8 + w8], 0u, tag);
  }
  __syncwarp();
  if (threadIdx.x == 0) TR(6);
  if (lane == 0) { ld_tagged_fast(&g_pflag[(b ^ 8) * 8 + w8], tag); asm volatile("fence.acq_rel.cta;" ::: "memory"); }
  __syncwarp();
  uint4 o[5];
  const uint4* inbox = g_part + ((b ^ 8) * 8 + w8) * 160 + lane;
#pragma unroll
  for (int j = 0; j < 5; j++) o[j] = __ldcg(inbox + j * 32);
  named_bar(3, 256);
  if (threadIdx.x == 0) TR(7);
#pragma unroll
  for (int j = 0; j < 5; j++)
    stsm_x4(base + OFF_A + j * 4096 + panel,
            pack_bf16(v[8 * j] + bf_lo(o[j].x), v[8 * j + 1] + bf_hi(o[j].x)), pack_bf16(v[8 * j + 2] + bf_lo(o[j].y), v[8 * j + 3] + bf_hi(o[j].y)),
            pack_bf16(v[8 * j + 4] + bf_lo(o[j].z), v[8 * j + 5] + bf_hi(o[j].z)), pack_bf16(v[8 * j + 6] + bf_lo(o[j].w), v[8 * j + 7] + bf_hi(o[j].w)));
  fence_async_smem();
  named_bar(3, 256);
  if (warp == 0 && lane == 0) {
#pragma unroll
    for (int j = 0; j < 5; j++) {
      if ((j & 1) != wg) continue;
      const int jj = KS * 10 + 2 * j;
      tma_store_2d(&p.tm_out, base + OFF_A + j * 4096, jj < 16 ? 128 * nt + 8 * jj : 512 + 32 * nt + 8 * (jj - 16), mt * 128);
    }
    bulk_commit();
    bulk_wait_read();
  }
  __syncwarp();
  if (threadIdx.x == 0) TR(27);
  cluster_wait();
}

__device__ __forceinline__ void attn_pair(uint32_t base, int w16, int lane, bool arrive = true) {
  const int r0 = (w16 >> 1) * 16, hp = w16 & 1;
  const int g = lane >> 2, q = lane & 3, mi = lane >> 3, r8 = lane & 7;
  const uint32_t stg = base + OFF_STG + hp * 80;
  const uint32_t qrow = stg + (r0 + (mi & 1) * 8 + r8) * QP;
  const uint32_t k0 = stg + max(r0 - 7 + r8, 0) * QP, k1 = stg + (r0 + 1 + r8) * QP, k2 = stg + min(r0 + 9 + r8, 127) * QP;
  const uint32_t pA = mi < 3 ? k0 + mi * 16 : k1, pB = mi < 2 ? k1 + 16 + mi * 16 : k2 + (mi - 2) * 16, pC = k2 + 32;
  uint32_t qa[2][4], qb[2][2], kf[2][9], vf[2][9];
#pragma unroll
  for (int h = 0; h < 2; h++) {
    ldsm_x4(qrow + (mi >> 1) * 16 + 32 * h, qa[h][0], qa[h][1], qa[h][2], qa[h][3]);
    ldsm_x2(qrow + 32 + 32 * h, qb[h][0], qb[h][1]);
    ldsm_x4(pA + 160 + 32 * h, kf[h][0], kf[h][1], kf[h][2], kf[h][3]);
    ldsm_x4(pB + 160 + 32 * h, kf[h][4], kf[h][5], kf[h][6], kf[h][7]);
    ldsm_x1(pC + 160 + 32 * h, kf[h][8]);
  }
  const bool d0 = 2 * q >= g, d1 = 2 * q + 1 >= g;
  const int key0 = r0 - 7 + 2 * q + (d0 ? 0 : 8), key1 = r0 - 6 + 2 * q + (d1 ? 0 : 8);
  const uint32_t r1a = base + OFF_R1;
  const float rk0 = lds_f(r1a + 4 * max(key0, 0)), rk1 = lds_f(r1a + 4 * max(key1, 0));
  const float rk2 = lds_f(r1a + 4 * (key0 + 8)), rk3 = lds_f(r1a + 4 * (key1 + 8));
  constexpr float SC = 0.22360679775f * 1.44269504089f;
  const float rq0 = SC * lds_f(r1a + 4 * (r0 + g)), rq1 = SC * lds_f(r1a + 4 * (r0 + g + 8));
  const float f0 = rq0 * rk0, f1 = rq0 * rk1, f2 = rq1 * rk2, f3 = rq1 * rk3;
  if (q >= 2) { qb[0][0] = 0; qb[0][1] = 0; } else { qa[1][0] = 0; qa[1][1] = 0; }
  float c[2][3][4];
#pragma unroll
  for (int h = 0; h < 2; h++)
#pragma unroll
    for (int t = 0; t < 3; t++) {
#pragma unroll
      for (int e = 0; e < 4; e++) c[h][t][e] = 0.f;
      mma_k16(c[h][t], qa[h][0], qa[h][1], qa[h][2], qa[h][3], kf[h][3 * t], kf[h][3 * t + 1]);
    }
#pragma unroll
  for (int h = 0; h < 2; h++)
#pragma unroll
    for (int t = 0; t < 3; t++) mma_k8(c[h][t], qb[h][0], qb[h][1], kf[h][3 * t + 2]);
#pragma unroll
  for (int h = 0; h < 2; h++) {
    ldsm_x4_t(pA + 320 + 32 * h, vf[h][0], vf[h][1], vf[h][2], vf[h][3]);
    ldsm_x4_t(pB + 320 + 32 * h, vf[h][4], vf[h][5], vf[h][6], vf[h][7]);
    ldsm_x1_t(pC + 320 + 32 * h, vf[h][8]);
  }
  float s[2][4];
#pragma unroll
  for (int h = 0; h < 2; h++) {
    s[h][0] = key0 >= 0 ? (d0 ? c[h][0][0] : c[h][1][0]) * f0 : -INFINITY;
    s[h][1] = key1 >= 0 ? (d1 ? c[h][0][1] : c[h][1][1]) * f1 : -INFINITY;
    s[h][2] = (d0 ? c[h][1][2] : c[h][2][2]) * f2;
    s[h][3] = (d1 ? c[h][1][3] : c[h][2][3]) * f3;
  }
  float m[2][2];
#pragma unroll
  for (int h = 0; h < 2; h++) { m[h][0] = fmaxf(s[h][0], s[h][1]); m[h][1] = fmaxf(s[h][2], s[h][3]); }
#pragma unroll
  for (int o = 1; o <= 2; o <<= 1)
#pragma unroll
    for (int h = 0; h < 2; h++) {
      m[h][0] = fmaxf(m[h][0], __shfl_xor_sync(0xffffffffu, m[h][0], o));
      m[h][1] = fmaxf(m[h][1], __shfl_xor_sync(0xffffffffu, m[h][1], o));
    }
#pragma unroll
  for (int h = 0; h < 2; h++) {
    s[h][0] = ex2(s[h][0] - m[h][0]); s[h][1] = ex2(s[h][1] - m[h][0]);
    s[h][2] = ex2(s[h][2] - m[h][1]); s[h][3] = ex2(s[h][3] - m[h][1]);
    m[h][0] = s[h][0] + s[h][1]; m[h][1] = s[h][2] + s[h][3];
  }
#pragma unroll
  for (int o = 1; o <= 2; o <<= 1)
#pragma unroll
    for (int h = 0; h < 2; h++) {
      m[h][0] += __shfl_xor_sync(0xffffffffu, m[h][0], o);
      m[h][1] += __shfl_xor_sync(0xffffffffu, m[h][1], o);
    }
  const uint32_t orow = base + OFF_O + (r0 + g) * 160 + hp * 80 + 4 * q;
#pragma unroll
  for (int h = 0; h < 2; h++) {
    const float i0 = rcp_fast(m[h][0]), i1 = rcp_fast(m[h][1]);
    const float p0 = s[h][0] * i0 * rk0, p1 = s[h][1] * i0 * rk1, p2 = s[h][2] * i1 * rk2, p3 = s[h][3] * i1 * rk3;
    const uint32_t pa0 = pack_bf16(d0 ? p0 : 0.f, d1 ? p1 : 0.f);
    const uint32_t pa2 = pack_bf16(d0 ? 0.f : p0, d1 ? 0.f : p1);
    const uint32_t pa3 = pack_bf16(d0 ? p2 : 0.f, d1 ? p3 : 0.f);
    const uint32_t pb1 = pack_bf16(d0 ? 0.f : p2, d1 ? 0.f : p3);
#pragma unroll
    for (int t = 0; t < 3; t++) {
#pragma unroll
      for (int e = 0; e < 4; e++) c[h][t][e] = 0.f;
      mma_k16(c[h][t], pa0, 0u, pa2, pa3, vf[h][t], vf[h][3 + t]);
      mma_k8(c[h][t], 0u, pb1, vf[h][6 + t]);
    }
  }
#pragma unroll
  for (int h = 0; h < 2; h++)
#pragma unroll
    for (int t = 0; t < 3; t++) {
      const bool ok = t == 1 || (t == 0 ? (h == 0 || q >= 2) : (h == 1 || q < 2));
      if (ok) {
        sts_u32(orow + 32 * h + 16 * t, pack_bf16(c[h][t][0], c[h][t][1]));
        sts_u32(orow + 8 * 160 + 32 * h + 16 * t, pack_bf16(c[h][t][2], c[h][t][3]));
      }
    }
  fence_async_smem();
  __syncwarp();
  if (lane == 0 && arrive) mbar_arrive(base + OFF_BAR + 8 * BAR_ATT);
}

__global__ void __cluster_dims__(2, 1, 1) __launch_bounds__(512, 1)
fused_block_kernel(const __grid_constant__ Params p) {
  extern __shared__ __align__(1024) uint8_t smem_raw[];
  const uint32_t base = smem_u32(smem_raw);
  const uint32_t bars = base + OFF_BAR;
  const int rank = blockIdx.x & 1;
  const int warp_id = __shfl_sync(0xffffffffu, threadIdx.x >> 5, 0), lane = threadIdx.x & 31;
  const int wg = warp_id >> 2, warp = warp_id & 3;

  int grp, idx;
  {
    uint32_t smid, nsmid;
    asm("mov.u32 %0, %%smid;" : "=r"(smid));
    asm("mov.u32 %0, %%nsmid;" : "=r"(nsmid));
    const int t = nsmid == NGRID ? smid >> 1 : blockIdx.x >> 1;
    if (t < 32) { grp = t & 7; idx = t >> 3; }
    else if (t < 60) { grp = 1 + (t - 32) % 7; idx = 4 + (t - 32) / 7; }
    else if (t < 62) return;
    else { grp = 0; idx = 4 + (t - 62); }
  }
  const int b = (grp * 8 + idx) * 2 + rank;
  const int trace_id = b; (void)trace_id;
  const int tb = 2 * (grp & 3) + (idx >> 2), nt1 = 4 * (grp >> 2) + (idx & 3);
  const int mt2 = 2 * grp + rank, nt2 = idx & 3, ks = idx >> 2;
  const int nh = ks == 0 ? 14 : 13, h0 = ks == 0 ? 0 : 14, o0 = ks * 5;
  const int nsteps2 = nh + 5;

  if (wg < 2) {
    reg_alloc<152>();
    named_bar(1, 288);
    cluster_arrive_relaxed();
    cluster_wait();
    {
      float acc[N1 / 2];
      mainloop1<N1>(acc, base, 0, rank, wg, lane, trace_id);
      if (threadIdx.x == 0) TR(8);
      mbar_wait(bars + 8 * BAR_MISC, 0);
      gelu_epilogue(acc, base, wg, warp, lane);
      __syncwarp();
      if (lane == 0) mbar_arrive(bars + 8 * BAR_STG_FULL);
      if (threadIdx.x == 0) TR(9);
    }
    {
      float acc[N2 / 2];
      mainloop1<N2>(acc, base, 10, rank, wg, lane, trace_id);
      if (threadIdx.x == 0) TR(10);
      mbar_wait(bars + 8 * BAR_STG_FREE, 0);
      dump_qkv(acc, base, wg, warp, lane);
      __syncwarp();
      if (lane == 0) mbar_arrive(bars + 8 * BAR_STG_FULL);
      if (threadIdx.x == 0) TR(11);
    }
    mbar_wait(bars + 8 * BAR_STG_FULL, 1);
    if (threadIdx.x == 0) TR(54);
    attn_pair(base, warp_id, lane);
    if (threadIdx.x == 0) TR(52);
    if (threadIdx.x == 96) TR(55);
    if (threadIdx.x == 160) TR(56);
    if (threadIdx.x == 224) TR(57);
    mbar_wait(bars + 8 * BAR_ATT, 0);
    if (threadIdx.x == 0) TR(53);
    {
      float acc[N3 / 2];
      int prev = 0;
      const uint32_t peer_empty2 = mapa(bars + 8 * BAR_P2_EMPTY, 1 - rank);
      const uint32_t a_lo = desc_lo(base + OFF_A + wg * 8192, 16), b_lo = desc_lo(base + OFF_B, 4096);
#pragma unroll 1
      for (int i = 0; i < nsteps2; i++) {
        const int q = i & 3;
        mbar_wait(bars + 8 * (BAR_P2_FULL + q), (i >> 2) & 1);
        if (threadIdx.x == 0 && i == 0) TR(12);
        const int sl = (q + 3) & 3;
        mma_step<N3>(acc, a_lo + sl * (A_SLOT >> 4), b_lo + sl * (3 * B_BLK >> 4), i > 0, i > 0 && i + 3 < nsteps2,
                     bars + 8 * (BAR_P2_EMPTY + prev), peer_empty2 + 8 * prev, lane);
        prev = q;
      }
      wgmma_wait<0>();
      acc_fence(acc);
      if (threadIdx.x == 0) TR(13);
      if (threadIdx.x == 0) {
        uint32_t peer_id;
        asm volatile("ld.shared::cluster.u32 %0, [%1];" : "=r"(peer_id) : "r"(mapa(base + OFF_ID, 1 - rank)));
        if (peer_id != (uint32_t)(grp * 8 + idx)) asm volatile("trap;");
      }
      if (ks == 0) final_epilogue<0>(acc, p, base, b, mt2, nt2, wg, warp, lane, trace_id);
      else final_epilogue<1>(acc, p, base, b, mt2, nt2, wg, warp, lane, trace_id);
      if (threadIdx.x == 0) { TR(14); atomicAdd(&g_cnt[CNT_EXIT], 1u); TR(15); }
    }
  } else {
    reg_dealloc<104>();
    if (warp_id == 8) {
      auto issue_p1 = [&](int g, int s) {
        const uint32_t full = bars + 8 * (BAR_P1_FULL + s);
        const uint32_t bdst = base + OFF_B + s * 4 * B_BLK + rank * 16384;
        const int k = g < 10 ? g : g - 10;
        mbar_expect_tx(full, g < 10 ? A_SLOT + 4 * B_BLK : A_SLOT + 2 * 15360);
        tma_3d(base + OFF_A + s * A_SLOT, &p.tm_x, k * 64, rank, tb * 128, full);
        if (g < 10) {
          tma_3d_mc(bdst, &p.tm_w1a, 0, k * 64 + rank * 32, 3 * nt1, full);
          tma_3d_mc(bdst + 3 * 4096, &p.tm_w1b, 0, k * 64 + rank * 32, nt1, full);
        } else {
          tma_4d_mc(bdst, &p.tm_qm, 0, k * 64 + rank * 32, nt1, 0, full);
          tma_4d_mc(bdst + 12288, &p.tm_qr, 64, k * 64 + rank * 32, nt1, 0, full);
        }
      };
      uint32_t epoch = 0;
      auto issue_p2 = [&](int i) {
        const int q = i & 3;
        if (i == 0) mbar_wait(bars + 8 * (BAR_P1_EMPTY + 2), 1);
        else if (i == 1) mbar_wait(bars + 8 * (BAR_P1_EMPTY + 0), 0);
        else if (i == 2) mbar_wait(bars + 8 * (BAR_P1_EMPTY + 1), 0);
        else if (i == 3) mbar_wait(bars + 8 * BAR_OFREE, 0);
        else if (i >= 4) mbar_wait(bars + 8 * (BAR_P2_EMPTY + q), ((i >> 2) & 1) ^ 1);
        const uint32_t full = bars + 8 * (BAR_P2_FULL + q);
        const uint32_t bb = base + OFF_B + ((q + 3) & 3) * 3 * B_BLK + rank * 12288;
        mbar_expect_tx(full, A_SLOT + 3 * B_BLK);
        const bool is_h = i < nh;
        const int krow = is_h ? (h0 + i) * 64 : (o0 + i - nh) * 64;
        tma_3d_mc(bb, is_h ? &p.tm_w2a : &p.tm_woa, 0, krow + rank * 32, 2 * nt2, full);
        tma_3d_mc(bb + 8192, is_h ? &p.tm_w2b : &p.tm_wob, 0, krow + rank * 32, nt2, full);
        if (i == 0) { wait_counter(&g_cnt[CNT_H + 32 * (mt2 >> 1)], (epoch + 1) * 16); fence_async_global(); TR(2); }
        if (i == nh) { TR(3); wait_counter(&g_cnt[CNT_O + 32 * (mt2 >> 1)], (epoch + 1) * 16); fence_async_global(); TR(4); }
        tma_2d(base + OFF_A + ((q + 3) & 3) * A_SLOT, &p.tm_act, is_h ? krow : FF + krow, mt2 * 128, full);
      };
      if (lane == 0) {
#pragma unroll
        for (int i = 0; i < BAR_COUNT; i++)
          mbar_init(bars + 8 * i, (i >= BAR_P1_EMPTY && i < BAR_P2_FULL) || (i >= BAR_P2_EMPTY && i < BAR_STG_FULL) || i == BAR_ATT ? 16
                                  : i == BAR_STG_FULL ? 8 : (i == BAR_XT || i == BAR_OFREE) ? 2 : 1);
        asm volatile("fence.mbarrier_init.release.cluster;" ::: "memory");
        if (base & 1023) asm volatile("trap;");
        asm volatile("st.shared.u32 [%0], %1;" :: "r"(base + OFF_ID), "r"(grp * 8 + idx) : "memory");
      }
      __syncwarp();
      named_arrive(1, 288);
      named_arrive(4, 256);
      cluster_arrive_relaxed();
      cluster_wait();
      if (lane == 0) {
#pragma unroll 1
        for (int g = 0; g < 3; g++) { issue_p1(g, g); if (g == 0) TR(61); }
        TR(1);
        epoch = ld_relaxed(&g_cnt[CNT_EXIT]) / NCTA;
        prefetch_tmap(&p.tm_qm); prefetch_tmap(&p.tm_qr); prefetch_tmap(&p.tm_act); prefetch_tmap(&p.tm_w2a); prefetch_tmap(&p.tm_w2b);
        prefetch_tmap(&p.tm_woa); prefetch_tmap(&p.tm_wob);
        int s = 0, ph = 0;
#pragma unroll 1
        for (int g = 3; g < 20; g++) {
          mbar_wait(bars + 8 * (BAR_P1_EMPTY + s), ph);
          issue_p1(g, s);
          if (g == 11) {
            l2_prefetch(reinterpret_cast<const uint8_t*>(p.w2) + b * 17280, 17280);
            l2_prefetch(reinterpret_cast<const uint8_t*>(p.wo) + b * 6400, 6400);
          }
          if (++s == 3) { s = 0; ph ^= 1; }
        }
        wait_counter(&g_cnt[CNT_START], (epoch + 1) * NCTA);
#pragma unroll 1
        for (int i = 0; i < 2; i++) issue_p2(i);
      }
      __syncwarp();
      mbar_wait(bars + 8 * BAR_STG_FULL, 1);
      if (lane == 0) TR(58);
      attn_pair(base, 8, lane);
      if (lane == 0) TR(59);
      if (lane == 0) {
#pragma unroll 1
        for (int i = 2; i < nsteps2; i++) issue_p2(i);
      }
      __syncwarp();
    } else {
      const int t = threadIdx.x - 288, sw = warp_id - 9;
      cluster_arrive_relaxed();
      if (t == 32) { prefetch_tmap(&p.tm_x); prefetch_tmap(&p.tm_w1a); prefetch_tmap(&p.tm_w1b); }
      const uint32_t epoch = ld_relaxed(&g_cnt[CNT_EXIT]) / NCTA;
      const uint32_t tag = epoch + 1;
      const long long t_start = clock64();
      named_bar(4, 256);
      const bool isw1 = b < 54;
      const int col0 = (isw1 ? b : b - 54) * 32;
      cluster_wait();
      if (sw == 6) {
        while (clock64() - t_start < PF_DELAY) {}
      }
      if (sw != 6) while (clock64() - t_start < SIDE_DELAY) {}
      if (sw == 6 && b < 114) {
        while (clock64() - t_start < SIDE_DELAY) {}
        if (lane == 0) mbar_expect_tx(bars + 8 * BAR_CS, 40960);
#pragma unroll 1
        for (int i = 0; i < 5; i++) {
          if (lane == 0) tma_2d(base + OFF_STG + i * 8192, isw1 ? &p.tm_c1 : &p.tm_c2, col0, i * 128, bars + 8 * BAR_CS);
          __syncwarp();
        }
      }

      uint4 xv[3][3];
#pragma unroll
      for (int r = 0; r < 3; r++) {
        const uint4* src = reinterpret_cast<const uint4*>(p.x + (size_t)(b * 16 + min(sw + 7 * r, 15)) * DM);
        xv[r][0] = __ldg(src + lane); xv[r][1] = __ldg(src + 32 + lane);
        xv[r][2] = __ldg(src + 64 + (lane & 15));
      }
      {
        float sh[3], a[3], q2[3];
#pragma unroll
        for (int r = 0; r < 3; r++) {
          sh[r] = __shfl_sync(0xffffffffu, bf_lo(xv[r][0].x), 0);
          float a0 = 0.f, a1 = 0.f, b0 = 0.f, b1 = 0.f;
#pragma unroll
          for (int c = 0; c < 3; c++) {
            const uint32_t u[4] = {xv[r][c].x, xv[r][c].y, xv[r][c].z, xv[r][c].w};
            const float live = (c < 2 || lane < 16) ? 1.f : 0.f;
#pragma unroll
            for (int e = 0; e < 4; e++) {
              float lo = bf_lo(u[e]) - sh[r], hi = bf_hi(u[e]) - sh[r];
              if (c == 2) { lo *= live; hi *= live; }
              a0 += lo; a1 += hi; b0 = fmaf(lo, lo, b0); b1 = fmaf(hi, hi, b1);
            }
          }
          a[r] = a0 + a1; q2[r] = b0 + b1;
        }
#pragma unroll
        for (int o = 16; o > 0; o >>= 1)
#pragma unroll
          for (int r = 0; r < 3; r++) { a[r] += __shfl_xor_sync(0xffffffffu, a[r], o); q2[r] += __shfl_xor_sync(0xffffffffu, q2[r], o); }
        if (lane < 3 && sw + 7 * lane < 16) {
          const float sa = lane == 0 ? a[0] : lane == 1 ? a[1] : a[2];
          const float sq = lane == 0 ? q2[0] : lane == 1 ? q2[1] : q2[2];
          const float s0 = lane == 0 ? sh[0] : lane == 1 ? sh[1] : sh[2];
          const float md = sa * (1.f / DM);
          const float var = fmaxf(sq * (1.f / DM) - md * md, 0.f);
          const float r1 = rsqrtf(var + 1e-5f);
          const float r2 = rsqrtf(var * r1 * r1 + 1e-5f);
          const int row = b * 16 + sw + 7 * lane;
          st_tagged(&g_stat[row], __float_as_uint(s0 + md), tag);
          st_tagged(&g_stat[S + row], __float_as_uint(r1), tag);
          st_tagged(&g_stat[2 * S + row], __float_as_uint(0.5f * r1 * r2), tag);
        }
      }
      __syncwarp();
      if (t == 0) TR(28);
      if (b < 114) {
        mbar_wait(bars + 8 * BAR_CS, 0);
        if (t == 0) TR(5);
        const uint32_t sa = base + OFF_STG + t * 16;
        uint4 v[12];
#pragma unroll
        for (int i = 0; i < 12; i++) v[i] = lds_u4(sa + ((i < 11 || t < 96) ? i : 0) * (NSIDE * 16));
        float a[8];
#pragma unroll
        for (int e = 0; e < 8; e++) a[e] = 0.f;
#pragma unroll
        for (int i = 0; i < 12; i++) {
          if (i < 11 || t < 96) {
            a[0] += bf_lo(v[i].x); a[1] += bf_hi(v[i].x); a[2] += bf_lo(v[i].y); a[3] += bf_hi(v[i].y);
            a[4] += bf_lo(v[i].z); a[5] += bf_hi(v[i].z); a[6] += bf_lo(v[i].w); a[7] += bf_hi(v[i].w);
          }
        }
#pragma unroll
        for (int o = 4; o <= 16; o <<= 1)
#pragma unroll
          for (int e = 0; e < 8; e++) a[e] += __shfl_xor_sync(0xffffffffu, a[e], o);
        const uint32_t red = base + OFF_CS2;
        if (lane < 4) {
          sts_f4(red + 4 * (sw * 32 + lane * 8), a[0], a[1], a[2], a[3]);
          sts_f4(red + 4 * (sw * 32 + lane * 8 + 4), a[4], a[5], a[6], a[7]);
        }
        named_bar(2, NSIDE);
        if (t < 32) {
          float sum = 0.f;
#pragma unroll
          for (int w7 = 0; w7 < 7; w7++) sum += lds_f(red + 4 * (w7 * 32 + t));
          st_tagged(g_cs + (isw1 ? 0 : FF) + col0 + t, __float_as_uint(sum), tag);
        }
      }
      if (t == 0) TR(29);
      named_bar(2, NSIDE);
      if (t == 0) asm volatile("red.relaxed.gpu.global.add.u32 [%0], 1;" :: "l"(&g_cnt[CNT_START]) : "memory");
      const int tok0 = tb * 256 + rank;
      mbar_wait(bars + 8 * BAR_GATE, 0);
      {
        const int tk = tok0 + 2 * (t & 127);
        const int c = t < 192 ? 192 * nt1 + t : 1536 + 24 * nt1 + min(t - 192, 23);
        unsigned long long w0 = ld_word(&g_stat[tk]), w1 = ld_word(&g_stat[S + tk]), w2 = ld_word(&g_stat[2 * S + tk]), w3 = ld_word(&g_cs[c]);
        const float bias = 0.5f * __bfloat162float(p.b1[c]);
        if ((w0 >> 32) != tag) w0 = ld_tagged(&g_stat[tk], tag);
        if ((w1 >> 32) != tag) w1 = ld_tagged(&g_stat[S + tk], tag);
        if ((w2 >> 32) != tag) w2 = ld_tagged(&g_stat[2 * S + tk], tag);
        if ((w3 >> 32) != tag) w3 = ld_tagged(&g_cs[c], tag);
        if (t < 128) {
          sts_u32(base + OFF_MEAN + 4 * t, (uint32_t)w0); sts_u32(base + OFF_R1 + 4 * t, (uint32_t)w1); sts_u32(base + OFF_RH + 4 * t, (uint32_t)w2);
        }
        if (t < N1) {
          sts_f(base + OFF_CB + 16 * (t >> 1) + 8 + 4 * (t & 1), bias);
          sts_u32(base + OFF_CB + 16 * (t >> 1) + 4 * (t & 1), (uint32_t)w3);
        }
      }
      if (t == 0) sts_u32(base + OFF_TAG, tag);
      named_bar(2, NSIDE);
      if (t == 0) { mbar_arrive(bars + 8 * BAR_MISC); TR(17); }

      mbar_wait(bars + 8 * BAR_STG_FULL, 0);
      if (t == 0) TR(19);
      if (t < N1) {
        const int cg = t % 27, rg = t / 27;
        bf16* hdst = g_act + (size_t)(tok0 + 2 * rg) * KACT + (cg < 24 ? 192 * nt1 + 8 * cg : 1536 + 24 * nt1 + 8 * (cg - 24));
        const uint32_t a = base + OFF_STG + t * 16;
        uint4 v = lds_u4(a);
#pragma unroll 1
        for (int it = 0; it < 16; it++) {
          const uint4 w = v;
          if (it < 15) v = lds_u4(a + (it + 1) * (8 * HP));
          *reinterpret_cast<uint4*>(hdst + (size_t)it * 16 * KACT) = w;
          if (it < 15) __nanosleep(H_GAP);
        }
      }
      for (int n = t; n < N2; n += NSIDE) {
        const int part = n < 192 ? n >> 6 : (n - 192) >> 4, c = n < 192 ? n & 63 : 64 + ((n - 192) & 15);
        sts_u32(base + OFF_CS2 + 4 * n, ld_tagged(&g_cs[FF + part * DM + nt1 * 80 + c], tag));
      }
      named_bar(2, NSIDE);
      if (t == 0) {
        mbar_arrive(bars + 8 * BAR_STG_FREE);
        TR(20);
        red_release(&g_cnt[CNT_H + 32 * tb]);
        TR(21);
      }
      __syncwarp();

      const int me = (tb * 2 + rank) * 8 + nt1;
      const int hw = t & 7, hi = (t >> 3) % 7, hh = (t >> 3) / 7, kr = hi - 7 + hw;
      const bool kvalid = tb > 0 || kr >= 0;
      const float rkey = kvalid ? __uint_as_float(ld_tagged(&g_stat[S + tok0 + 2 * kr], tag)) : 0.f;
      mbar_wait(bars + 8 * BAR_STG_FULL, 1);
      if (t == 0) TR(22);
      if (tb < 7) {
        uint32_t hv[3];
#pragma unroll
        for (int i = 0; i < 3; i++) { const int c = min(t + i * NSIDE, 559); hv[i] = lds_u32(base + OFF_STG + (121 + c / 80) * QP + 160 + (c % 80) * 4); }
#pragma unroll
        for (int i = 0; i < 3; i++) if (t + i * NSIDE < 560) st_tagged(&g_halo[me * 560 + t + i * NSIDE], hv[i], tag);
      }
      attn_pair(base, warp_id, lane);
      if (t == 0) TR(23);
      if (t == 192) {
        mbar_wait(bars + 8 * BAR_ATT, 0);
        tma_store_3d(&p.tm_ost, base + OFF_O + 7 * 160, FF + nt1 * 80, rank, tb * 128 + 7);
        bulk_commit();
        bulk_wait_read();
        mbar_arrive(bars + 8 * BAR_OFREE);
        mbar_arrive_remote(mapa(bars + 8 * BAR_OFREE, 1 - rank));
      }
      __syncwarp();
      if (tb > 0) {
        unsigned long long hw3[3];
#pragma unroll
        for (int i = 0; i < 3; i++) hw3[i] = ld_word(&g_halo[(me - 16) * 560 + min(t + i * NSIDE, 559)]);
#pragma unroll
        for (int i = 0; i < 3; i++) {
          const int c = t + i * NSIDE;
          if (c < 560) sts_u32(base + OFF_HALO + c * 4, (hw3[i] >> 32) == tag ? (uint32_t)hw3[i] : ld_tagged(&g_halo[(me - 16) * 560 + c], tag));
        }
      } else {
        for (int c = t; c < 560; c += NSIDE) sts_u32(base + OFF_HALO + c * 4, 0u);
      }
      named_bar(2, NSIDE);
      if (t == 0) TR(24);
      {
        const uint32_t qa = base + OFF_STG + hi * QP + hh * 40;
        const uint32_t ka = kr >= 0 ? base + OFF_STG + kr * QP + 160 + hh * 40 : base + OFF_HALO + (kr + 7) * 320 + hh * 40;
        float s0 = 0.f, s1 = 0.f;
#pragma unroll
        for (int c = 0; c < 5; c++) {
          const uint2 a = lds_u2(qa + 8 * c), k = lds_u2(ka + 8 * c);
          s0 = fmaf(bf_lo(a.x), bf_lo(k.x), s0); s1 = fmaf(bf_hi(a.x), bf_hi(k.x), s1);
          s0 = fmaf(bf_lo(a.y), bf_lo(k.y), s0); s1 = fmaf(bf_hi(a.y), bf_hi(k.y), s1);
        }
        float sc = kvalid ? (s0 + s1) * (0.22360679775f * 1.44269504089f) * lds_f(base + OFF_R1 + 4 * hi) * rkey : -INFINITY;
        float mx = sc;
#pragma unroll
        for (int o = 1; o < 8; o <<= 1) mx = fmaxf(mx, __shfl_xor_sync(0xffffffffu, mx, o));
        sc = ex2(sc - mx);
        float sum = sc;
#pragma unroll
        for (int o = 1; o < 8; o <<= 1) sum += __shfl_xor_sync(0xffffffffu, sum, o);
        sc = __bfloat162float(__float2bfloat16(sc * rcp_fast(sum) * rkey));
        float o0 = 0.f, o1 = 0.f, o2 = 0.f, o3 = 0.f;
#pragma unroll
        for (int j = 0; j < 8; j++) {
          const float pj = __shfl_sync(0xffffffffu, sc, (lane & 24) + j);
          const int vr = hi - 7 + j;
          const uint32_t va = (vr >= 0 ? base + OFF_STG + vr * QP + 320 : base + OFF_HALO + (vr + 7) * 320 + 160) + hh * 40 + 4 * hw;
          const uint32_t u = lds_u32(va);
          o0 = fmaf(pj, bf_lo(u), o0); o1 = fmaf(pj, bf_hi(u), o1);
          if (hw < 2) { const uint32_t u2 = lds_u32(va + 32); o2 = fmaf(pj, bf_lo(u2), o2); o3 = fmaf(pj, bf_hi(u2), o3); }
        }
        uint32_t* od = reinterpret_cast<uint32_t*>(g_act + (size_t)(tok0 + 2 * hi) * KACT + FF + nt1 * 80 + hh * 20);
        od[hw] = pack_bf16(o0, o1);
        if (hw < 2) od[8 + hw] = pack_bf16(o2, o3);
      }
      if (t == 192) bulk_wait();
      named_bar(2, NSIDE);
      if (t == 0) {
        red_release(&g_cnt[CNT_O + 32 * tb]);
        TR(26);
      }
      __syncwarp();
      if (t == 32) {
        mbar_expect_tx(bars + 8 * BAR_XT, 20480);
#pragma unroll 1
        for (int j = 0; j < 5; j++) {
          const int jj = ks * 10 + 2 * j;
          tma_2d(base + OFF_XT + j * 4096, &p.tm_xt, jj < 16 ? 128 * nt2 + 8 * jj : 512 + 32 * nt2 + 8 * (jj - 16), mt2 * 128, bars + 8 * BAR_XT);
        }
      }
      if (t >= 64 && t < 144) {
        const int n = t - 64, jj = ks * 10 + (n >> 3);
        const int col = (jj < 16 ? 128 * nt2 + 8 * jj : 512 + 32 * nt2 + 8 * (jj - 16)) + (n & 7);
        sts_f(base + OFF_B2 + 4 * n, __bfloat162float(p.b2[col]));
      }
      named_bar(2, NSIDE);
      if (t == 0) mbar_arrive(bars + 8 * BAR_XT);
    }
  }
}

typedef CUresult (*EncodeFn)(CUtensorMap*, CUtensorMapDataType, cuuint32_t, void*, const cuuint64_t*, const cuuint64_t*,
                             const cuuint32_t*, const cuuint32_t*, CUtensorMapInterleave, CUtensorMapSwizzle,
                             CUtensorMapL2promotion, CUtensorMapFloatOOBfill);

static void make_map(EncodeFn fn, CUtensorMap* m, const void* ptr, int rank, const cuuint64_t* dims, const cuuint64_t* strides,
                     const cuuint32_t* box, CUtensorMapSwizzle swz) {
  cuuint32_t es[4] = {1, 1, 1, 1};
  fn(m, CU_TENSOR_MAP_DATA_TYPE_BFLOAT16, rank, const_cast<void*>(ptr), dims, strides, box, es, CU_TENSOR_MAP_INTERLEAVE_NONE,
     swz, CU_TENSOR_MAP_L2_PROMOTION_L2_128B, CU_TENSOR_MAP_FLOAT_OOB_FILL_NONE);
}

extern "C" void kernel_launch(void* const* d_in, const int* in_sizes, int n_in, void* d_out, int out_size) {
  (void)in_sizes; (void)n_in; (void)out_size;
  const bf16* x = (const bf16*)d_in[0];
  const bf16* wqkv = (const bf16*)d_in[1];
  const bf16* wo = (const bf16*)d_in[2];
  const bf16* w1 = (const bf16*)d_in[4];
  const bf16* b1 = (const bf16*)d_in[5];
  const bf16* w2 = (const bf16*)d_in[6];
  const bf16* b2 = (const bf16*)d_in[7];

  static EncodeFn fn = nullptr;
  static void* act = nullptr;
  if (!fn) {
    void* f = nullptr;
    cudaDriverEntryPointQueryResult qr;
    cudaGetDriverEntryPoint("cuTensorMapEncodeTiled", &f, cudaEnableDefault, &qr);
    fn = (EncodeFn)f;
    cudaGetSymbolAddress(&act, g_act);
    cudaFuncSetAttribute(fused_block_kernel, cudaFuncAttributeMaxDynamicSharedMemorySize, SMEM_LAUNCH);
  }
  const CUtensorMapSwizzle SW128 = CU_TENSOR_MAP_SWIZZLE_128B, SW32 = CU_TENSOR_MAP_SWIZZLE_32B, SWN = CU_TENSOR_MAP_SWIZZLE_NONE;
  Params p;
  { cuuint64_t d[3] = {DM, 2, S / 2}, s[2] = {DM * 2, DM * 4}; cuuint32_t bx[3] = {64, 1, 128}; make_map(fn, &p.tm_x, x, 3, d, s, bx, SW128); }
  { cuuint64_t d[3] = {64, DM, 27}, s[2] = {FF * 2, 128}; cuuint32_t bx[3] = {64, 32, 3}; make_map(fn, &p.tm_w1a, w1, 3, d, s, bx, SW128); }
  { cuuint64_t d[3] = {24, DM, 8}, s[2] = {FF * 2, 48}; cuuint32_t bx[3] = {64, 32, 1}; make_map(fn, &p.tm_w1b, w1 + 1536, 3, d, s, bx, SW128); }
  { cuuint64_t d[4] = {80, DM, 8, 3}, s[3] = {NQKV * 2, 160, DM * 2}; cuuint32_t bx[4] = {64, 32, 1, 3}; make_map(fn, &p.tm_qm, wqkv, 4, d, s, bx, SW128); }
  { cuuint64_t d[4] = {80, DM, 8, 3}, s[3] = {NQKV * 2, 160, DM * 2}; cuuint32_t bx[4] = {16, 32, 1, 3}; make_map(fn, &p.tm_qr, wqkv, 4, d, s, bx, SW32); }
  { cuuint64_t d[2] = {KACT, S}, s[1] = {KACT * 2}; cuuint32_t bx[2] = {64, 128}; make_map(fn, &p.tm_act, act, 2, d, s, bx, SW128); }
  { cuuint64_t d[3] = {64, FF, 10}, s[2] = {DM * 2, 128}; cuuint32_t bx[3] = {64, 32, 2}; make_map(fn, &p.tm_w2a, w2, 3, d, s, bx, SW128); }
  { cuuint64_t d[3] = {32, FF, 4}, s[2] = {DM * 2, 64}; cuuint32_t bx[3] = {64, 32, 1}; make_map(fn, &p.tm_w2b, w2 + 512, 3, d, s, bx, SW128); }
  { cuuint64_t d[3] = {64, DM, 10}, s[2] = {DM * 2, 128}; cuuint32_t bx[3] = {64, 32, 2}; make_map(fn, &p.tm_woa, wo, 3, d, s, bx, SW128); }
  { cuuint64_t d[3] = {32, DM, 4}, s[2] = {DM * 2, 64}; cuuint32_t bx[3] = {64, 32, 1}; make_map(fn, &p.tm_wob, wo + 512, 3, d, s, bx, SW128); }
  { cuuint64_t d[2] = {FF, DM}, s[1] = {FF * 2}; cuuint32_t bx[2] = {32, 128}; make_map(fn, &p.tm_c1, w1, 2, d, s, bx, SWN); }
  { cuuint64_t d[2] = {NQKV, DM}, s[1] = {NQKV * 2}; cuuint32_t bx[2] = {32, 128}; make_map(fn, &p.tm_c2, wqkv, 2, d, s, bx, SWN); }
  { cuuint64_t d[2] = {DM, S}, s[1] = {DM * 2}; cuuint32_t bx[2] = {16, 128}; make_map(fn, &p.tm_xt, x, 2, d, s, bx, SWN); }
  { cuuint64_t d[2] = {DM, S}, s[1] = {DM * 2}; cuuint32_t bx[2] = {16, 128}; make_map(fn, &p.tm_out, d_out, 2, d, s, bx, SWN); }
  { cuuint64_t d[3] = {KACT, 2, S / 2}, s[2] = {KACT * 2, KACT * 4}; cuuint32_t bx[3] = {80, 1, 121}; make_map(fn, &p.tm_ost, act, 3, d, s, bx, SWN); }
  p.x = x; p.w1 = w1; p.wqkv = wqkv; p.w2 = w2; p.wo = wo; p.b1 = b1; p.b2 = b2; p.out = (bf16*)d_out;
  fused_block_kernel<<<NGRID, 512, SMEM_LAUNCH, cudaStreamPerThread>>>(p);
}
```

```cpp
#include <cuda_runtime.h>
#include <cuda_bf16.h>
#include <cuda.h>
#include <stdint.h>

typedef __nv_bfloat16 bf16;

constexpr int S = 2048, DM = 640, FF = 1728, NQKV = 1920, KACT = FF + DM;
constexpr int NCTA = 128, NGRID = 132;
constexpr int N1 = 216, N2 = 240, N3 = 160;
constexpr int NSIDE = 224;

constexpr int A_SLOT = 16384;
constexpr int B_BLK = 8192;
constexpr int QP = 496;
constexpr int OFF_A = 0;
constexpr int OFF_B = 4 * A_SLOT;
constexpr int OFF_STG = OFF_B + 12 * B_BLK;
constexpr int OFF_HL = OFF_STG + 3 * 16384;
constexpr int OFF_BAR = OFF_STG + 128 * QP;
constexpr int OFF_ID = OFF_BAR + 224;
constexpr int OFF_TAG = OFF_BAR + 228;
constexpr int OFF_R1 = OFF_BAR + 240;
constexpr int OFF_MEAN = OFF_R1 + 512;
constexpr int OFF_RH = OFF_MEAN + 512;
constexpr int OFF_CB = OFF_RH + 512;
constexpr int OFF_CS2 = OFF_CB + 1728;
constexpr int OFF_XT = OFF_STG;
constexpr int OFF_B2 = OFF_XT + 20480;
constexpr int OFF_SEND = OFF_STG + 21504;
constexpr int OFF_OUT = OFF_SEND + 20480;
constexpr int OFF_O = OFF_B + 6 * B_BLK + 32;
constexpr int OFF_HALO = OFF_MEAN;
constexpr int OFF_O7 = (OFF_HALO + 7 * 320 + 127) / 128 * 128;
constexpr int SMEM_BYTES = OFF_CS2 + 960;
static_assert(OFF_O7 + 7 * 160 <= SMEM_BYTES, "smem layout");
static_assert(OFF_HALO + 7 * 320 <= OFF_CS2 + 960 && SMEM_BYTES + 512 <= 232448 && OFF_HALO % 16 == 0, "smem layout");
#define GATE_STEP 6
#define SIDE_DELAY 300
#define LPF_K 0
#define GO_DELAY_NS 1200
#define PRE_P2 3
#define TPF_K 0
#define CS_ROWS 64
#define CS_GAP 200
#define CS_FIRST 1
#define PF_W1 0
#define PF_WQ 0
#define PF_DELAY 0
#define PF2_DELAY 2200
#define CS_DELAY 0
#define H_ROWS 128
#define H_GAP 900

enum {
  BAR_P1_FULL = 0, BAR_P1_EMPTY = 3, BAR_P2_FULL = 6, BAR_P2_EMPTY = 10, BAR_STG_FULL = 14, BAR_STG_FREE = 15,
  BAR_MISC = 16, BAR_PEER_FREE = 17, BAR_PART = 18, BAR_ATT = 19, BAR_XT = 20, BAR_CS = 21, BAR_OFREE = 22, BAR_GATE = 23, BAR_OMAIN = 24, BAR_GO = 25, BAR_R1END = 26, BAR_GO2 = 27, BAR_COUNT = 28
};

enum { CNT_EXIT = 0, CNT_START = 32, CNT_H = 64, CNT_O = 64 + 8 * 32, CNT_TOTAL = 64 + 16 * 32 };

__device__ __align__(1024) bf16 g_act[(size_t)S * KACT];
__device__ unsigned long long g_stat[3 * S];
__device__ unsigned long long g_cs[FF + NQKV];
__device__ uint4 g_part[128 * 8 * 160];
__device__ unsigned long long g_pflag[128 * 8];
__device__ unsigned long long g_sync[2 * 128];
__device__ unsigned long long g_halo[128 * 560];
__device__ unsigned int g_cnt[CNT_TOTAL];
#define TR(slot) do {} while (0)
constexpr int SMEM_LAUNCH = SMEM_BYTES;

struct Params {
  alignas(64) CUtensorMap tm_x;
  alignas(64) CUtensorMap tm_w1a;
  alignas(64) CUtensorMap tm_w1b;
  alignas(64) CUtensorMap tm_qm;
  alignas(64) CUtensorMap tm_qr;
  alignas(64) CUtensorMap tm_c1;
  alignas(64) CUtensorMap tm_c2;
  alignas(64) CUtensorMap tm_hst;
  alignas(64) CUtensorMap tm_hsl;
  alignas(64) CUtensorMap tm_os7;
  alignas(64) CUtensorMap tm_ost;
  alignas(64) CUtensorMap tm_o80, tm_o48, tm_o32;
  alignas(64) CUtensorMap tm_act;
  alignas(64) CUtensorMap tm_w2a;
  alignas(64) CUtensorMap tm_w2b;
  alignas(64) CUtensorMap tm_woa;
  alignas(64) CUtensorMap tm_wob;
  const bf16* x; const bf16* w1; const bf16* wqkv; const bf16* w2; const bf16* wo; const bf16* b1; const bf16* b2;
  bf16* out;
};

__device__ __forceinline__ long long gtime() { long long t; asm volatile("mov.u64 %0, %%globaltimer;" : "=l"(t)); return t; }
__device__ __forceinline__ uint32_t gtime_lo() { uint32_t t; asm volatile("mov.u32 %0, %%globaltimer_lo;" : "=r"(t)); return t; }
__device__ __forceinline__ uint32_t smem_u32(const void* p) { return (uint32_t)__cvta_generic_to_shared(p); }
__device__ __forceinline__ void mbar_init(uint32_t bar, uint32_t cnt) { asm volatile("mbarrier.init.shared::cta.b64 [%0], %1;" :: "r"(bar), "r"(cnt) : "memory"); }
__device__ __forceinline__ void mbar_expect_tx(uint32_t bar, uint32_t bytes) { asm volatile("mbarrier.arrive.expect_tx.shared::cta.b64 _, [%0], %1;" :: "r"(bar), "r"(bytes) : "memory"); }
__device__ __forceinline__ void mbar_arrive(uint32_t bar) { asm volatile("mbarrier.arrive.shared::cta.b64 _, [%0];" :: "r"(bar) : "memory"); }
__device__ __forceinline__ uint32_t mapa(uint32_t addr, uint32_t cta) { uint32_t r; asm volatile("mapa.shared::cluster.u32 %0, %1, %2;" : "=r"(r) : "r"(addr), "r"(cta)); return r; }
__device__ __forceinline__ void mbar_arrive_remote(uint32_t remote_bar) { asm volatile("mbarrier.arrive.shared::cluster.b64 _, [%0];" :: "r"(remote_bar) : "memory"); }
__device__ __forceinline__ void mbar_wait(uint32_t bar, uint32_t parity) {
  asm volatile("{\n.reg .pred p, q;\n.reg .u32 n;\nmov.u32 n, 0;\n"
               "MB_LOOP:\nmbarrier.try_wait.parity.shared::cta.b64 p, [%0], %1, 20000;\n@p bra MB_DONE;\n"
               "add.u32 n, n, 1;\nsetp.gt.u32 q, n, 200000;\n@q trap;\nbra MB_LOOP;\nMB_DONE:\n}"
               :: "r"(bar), "r"(parity) : "memory");
}
__device__ __forceinline__ uint32_t ld_acquire(const unsigned int* p) { uint32_t v; asm volatile("ld.acquire.gpu.global.u32 %0, [%1];" : "=r"(v) : "l"(p) : "memory"); return v; }
__device__ __forceinline__ uint32_t ld_relaxed(const unsigned int* p) { uint32_t v; asm volatile("ld.relaxed.gpu.global.u32 %0, [%1];" : "=r"(v) : "l"(p) : "memory"); return v; }
__device__ __forceinline__ void red_after_bulk(unsigned int* p) { asm volatile("fence.proxy.async;\nred.relaxed.gpu.global.add.u32 [%0], 1;" :: "l"(p) : "memory"); }
__device__ __forceinline__ void red_release(unsigned int* p) { asm volatile("red.release.gpu.global.add.u32 [%0], 1;" :: "l"(p) : "memory"); }
__device__ __forceinline__ void wait_counter(const unsigned int* ptr, uint32_t target) {
  asm volatile("{\n.reg .pred p, q;\n.reg .u32 n, v;\n.reg .s32 d;\nmov.u32 n, 0;\n"
               "WC_LOOP:\nld.acquire.gpu.global.u32 v, [%0];\nsub.s32 d, v, %1;\nsetp.ge.s32 p, d, 0;\n@p bra WC_DONE;\n"
               "add.u32 n, n, 1;\nsetp.gt.u32 q, n, 4000000;\n@q trap;\nbra WC_LOOP;\nWC_DONE:\n}"
               :: "l"(ptr), "r"(target) : "memory");
}
__device__ __forceinline__ void st_tagged(unsigned long long* ptr, uint32_t v, uint32_t tag) {
  asm volatile("st.relaxed.gpu.global.b64 [%0], %1;" :: "l"(ptr), "l"((unsigned long long)v | ((unsigned long long)tag << 32)) : "memory");
}
__device__ __forceinline__ uint32_t ld_tagged(const unsigned long long* ptr, uint32_t tag) {
  uint32_t v;
  asm volatile("{\n.reg .pred p, q;\n.reg .u32 n, t;\n.reg .b64 w;\nmov.u32 n, 0;\n"
               "LT_LOOP:\nld.relaxed.gpu.global.b64 w, [%1];\nmov.b64 {%0, t}, w;\nsetp.eq.u32 p, t, %2;\n@p bra LT_DONE;\n"
               "nanosleep.u32 100;\nadd.u32 n, n, 1;\nsetp.gt.u32 q, n, 2000000;\n@q trap;\nbra LT_LOOP;\nLT_DONE:\n}"
               : "=r"(v) : "l"(ptr), "r"(tag) : "memory");
  return v;
}
__device__ __forceinline__ uint32_t ld_tagged_fast(const unsigned long long* ptr, uint32_t tag) {
  uint32_t v;
  asm volatile("{\n.reg .pred p, q;\n.reg .u32 n, t;\n.reg .b64 w;\nmov.u32 n, 0;\n"
               "LF_LOOP:\nld.relaxed.gpu.global.b64 w, [%1];\nmov.b64 {%0, t}, w;\nsetp.eq.u32 p, t, %2;\n@p bra LF_DONE;\n"
               "add.u32 n, n, 1;\nsetp.gt.u32 q, n, 4000000;\n@q trap;\nbra LF_LOOP;\nLF_DONE:\n}"
               : "=r"(v) : "l"(ptr), "r"(tag) : "memory");
  return v;
}
__device__ __forceinline__ unsigned long long ld_word(const unsigned long long* ptr) {
  unsigned long long w;
  asm volatile("ld.relaxed.gpu.global.b64 %0, [%1];" : "=l"(w) : "l"(ptr) : "memory");
  return w;
}
__device__ __forceinline__ void bulk_store(void* gptr, uint32_t src, uint32_t bytes) {
  asm volatile("cp.async.bulk.global.shared::cta.bulk_group [%0], [%1], %2;" :: "l"(gptr), "r"(src), "r"(bytes) : "memory");
}
__device__ __forceinline__ uint32_t lds_u32(uint32_t a) { uint32_t v; asm volatile("ld.shared.u32 %0, [%1];" : "=r"(v) : "r"(a)); return v; }
__device__ __forceinline__ void fence_async_smem() { asm volatile("fence.proxy.async.shared::cta;" ::: "memory"); }
__device__ __forceinline__ void fence_async_global() { asm volatile("fence.proxy.async.global;" ::: "memory"); }
__device__ __forceinline__ void named_bar(int id, int n) { asm volatile("bar.sync %0, %1;" :: "r"(id), "r"(n) : "memory"); }
__device__ __forceinline__ void tma_2d(uint32_t dst, const CUtensorMap* tm, int c0, int c1, uint32_t bar) {
  asm volatile("cp.async.bulk.tensor.2d.shared::cluster.global.mbarrier::complete_tx::bytes [%0], [%1, {%3, %4}], [%2];"
    :: "r"(dst), "l"(tm), "r"(bar), "r"(c0), "r"(c1) : "memory");
}
__device__ __forceinline__ void tma_3d(uint32_t dst, const CUtensorMap* tm, int c0, int c1, int c2, uint32_t bar) {
  asm volatile("cp.async.bulk.tensor.3d.shared::cluster.global.mbarrier::complete_tx::bytes [%0], [%1, {%3, %4, %5}], [%2];"
    :: "r"(dst), "l"(tm), "r"(bar), "r"(c0), "r"(c1), "r"(c2) : "memory");
}
__device__ __forceinline__ void tma_3d_mc(uint32_t dst, const CUtensorMap* tm, int c0, int c1, int c2, uint32_t bar) {
  asm volatile("cp.async.bulk.tensor.3d.shared::cluster.global.mbarrier::complete_tx::bytes.multicast::cluster [%0], [%1, {%3, %4, %5}], [%2], %6;"
    :: "r"(dst), "l"(tm), "r"(bar), "r"(c0), "r"(c1), "r"(c2), "h"((uint16_t)3) : "memory");
}
__device__ __forceinline__ void tma_4d_mc(uint32_t dst, const CUtensorMap* tm, int c0, int c1, int c2, int c3, uint32_t bar) {
  asm volatile("cp.async.bulk.tensor.4d.shared::cluster.global.mbarrier::complete_tx::bytes.multicast::cluster [%0], [%1, {%3, %4, %5, %6}], [%2], %7;"
    :: "r"(dst), "l"(tm), "r"(bar), "r"(c0), "r"(c1), "r"(c2), "r"(c3), "h"((uint16_t)3) : "memory");
}
__device__ __forceinline__ void tma_4d(uint32_t dst, const CUtensorMap* tm, int c0, int c1, int c2, int c3, uint32_t bar) {
  asm volatile("cp.async.bulk.tensor.4d.shared::cluster.global.mbarrier::complete_tx::bytes [%0], [%1, {%3, %4, %5, %6}], [%2];"
    :: "r"(dst), "l"(tm), "r"(bar), "r"(c0), "r"(c1), "r"(c2), "r"(c3) : "memory");
}
__device__ __forceinline__ void tma_store_2d(const CUtensorMap* tm, uint32_t src, int c0, int c1) {
  asm volatile("cp.async.bulk.tensor.2d.global.shared::cta.bulk_group [%0, {%2, %3}], [%1];"
    :: "l"(tm), "r"(src), "r"(c0), "r"(c1) : "memory");
}
__device__ __forceinline__ void tma_store_4d(const CUtensorMap* tm, uint32_t src, int c0, int c1, int c2, int c3) {
  asm volatile("cp.async.bulk.tensor.4d.global.shared::cta.bulk_group [%0, {%2, %3, %4, %5}], [%1];"
    :: "l"(tm), "r"(src), "r"(c0), "r"(c1), "r"(c2), "r"(c3) : "memory");
}
__device__ __forceinline__ void bulk_load(uint32_t dst, const void* src, uint32_t bytes, uint32_t bar) {
  asm volatile("cp.async.bulk.shared::cluster.global.mbarrier::complete_tx::bytes [%0], [%1], %2, [%3];"
    :: "r"(dst), "l"(src), "r"(bytes), "r"(bar) : "memory");
}
__device__ __forceinline__ void tma_store_3d(const CUtensorMap* tm, uint32_t src, int c0, int c1, int c2) {
  asm volatile("cp.async.bulk.tensor.3d.global.shared::cta.bulk_group [%0, {%2, %3, %4}], [%1];"
    :: "l"(tm), "r"(src), "r"(c0), "r"(c1), "r"(c2) : "memory");
}
__device__ __forceinline__ void bulk_commit() { asm volatile("cp.async.bulk.commit_group;" ::: "memory"); }
__device__ __forceinline__ void bulk_wait_read() { asm volatile("cp.async.bulk.wait_group.read 0;" ::: "memory"); }
__device__ __forceinline__ void bulk_wait() { asm volatile("cp.async.bulk.wait_group 0;" ::: "memory"); }
__device__ __forceinline__ void l2_prefetch(const void* p, uint32_t bytes) { asm volatile("cp.async.bulk.prefetch.L2.global [%0], %1;" :: "l"(p), "r"(bytes) : "memory"); }
__device__ __forceinline__ void tma_prefetch_3d(const CUtensorMap* tm, int c0, int c1, int c2) {
  asm volatile("cp.async.bulk.prefetch.tensor.3d.L2.global.tile [%0, {%1, %2, %3}];" :: "l"(tm), "r"(c0), "r"(c1), "r"(c2) : "memory");
}
__device__ __forceinline__ void prefetch_l2(const void* p) { asm volatile("prefetch.global.L2 [%0];" :: "l"(p) : "memory"); }
__device__ __forceinline__ void touch_line(const void* p) {
  [[maybe_unused]] uint32_t v;
  asm volatile("ld.global.nc.L2::128B.u32 %0, [%1];" : "=r"(v) : "l"(reinterpret_cast<const void*>(reinterpret_cast<uintptr_t>(p) & ~(uintptr_t)3)));
}
__device__ __forceinline__ void prefetch_tmap(const CUtensorMap* tm) { asm volatile("prefetch.tensormap [%0];" :: "l"(tm) : "memory"); }
__device__ __forceinline__ void wgmma_fence() { asm volatile("wgmma.fence.sync.aligned;" ::: "memory"); }
__device__ __forceinline__ void wgmma_commit() { asm volatile("wgmma.commit_group.sync.aligned;" ::: "memory"); }
template <int N> __device__ __forceinline__ void wgmma_wait() { asm volatile("wgmma.wait_group.sync.aligned %0;" :: "n"(N) : "memory"); }
__device__ __forceinline__ uint32_t desc_lo(uint32_t addr, uint32_t lbo) { return ((addr & 0x3FFFF) >> 4) | ((lbo >> 4) << 16); }
constexpr uint32_t DESC_HI_128 = (1024 >> 4) | (1u << 30), DESC_HI_32 = (256 >> 4) | (3u << 30);
__device__ __forceinline__ uint64_t desc(uint32_t lo, uint32_t hi) { return ((uint64_t)hi << 32) | lo; }
template <int R> __device__ __forceinline__ void reg_alloc() { asm volatile("setmaxnreg.inc.sync.aligned.u32 %0;" :: "n"(R)); }
template <int R> __device__ __forceinline__ void reg_dealloc() { asm volatile("setmaxnreg.dec.sync.aligned.u32 %0;" :: "n"(R)); }
__device__ __forceinline__ uint32_t pack_bf16(float lo, float hi) { uint32_t r; asm("cvt.rn.bf16x2.f32 %0, %1, %2;" : "=r"(r) : "f"(hi), "f"(lo)); return r; }
__device__ __forceinline__ float bf_lo(uint32_t v) { return __uint_as_float(v << 16); }
__device__ __forceinline__ float bf_hi(uint32_t v) { return __uint_as_float(v & 0xffff0000u); }
__device__ __forceinline__ void stsm_x4(uint32_t addr, uint32_t a, uint32_t b, uint32_t c, uint32_t d) {
  asm volatile("stmatrix.sync.aligned.m8n8.x4.shared.b16 [%0], {%1, %2, %3, %4};" :: "r"(addr), "r"(a), "r"(b), "r"(c), "r"(d) : "memory");
}
__device__ __forceinline__ void stsm_x2(uint32_t addr, uint32_t a, uint32_t b) {
  asm volatile("stmatrix.sync.aligned.m8n8.x2.shared.b16 [%0], {%1, %2};" :: "r"(addr), "r"(a), "r"(b) : "memory");
}
__device__ __forceinline__ float2 lds_f2(uint32_t a) { float2 v; asm volatile("ld.shared.v2.f32 {%0, %1}, [%2];" : "=f"(v.x), "=f"(v.y) : "r"(a)); return v; }
__device__ __forceinline__ float lds_f(uint32_t a) { float v; asm volatile("ld.shared.f32 %0, [%1];" : "=f"(v) : "r"(a)); return v; }
__device__ __forceinline__ uint32_t launder(uint32_t a) { asm volatile("" : "+r"(a) :: "memory"); return a; }
__device__ __forceinline__ float2 lds_f2_nv(uint32_t a) { float2 v; asm("ld.shared.v2.f32 {%0, %1}, [%2];" : "=f"(v.x), "=f"(v.y) : "r"(a)); return v; }
__device__ __forceinline__ float4 lds_f4_nv(uint32_t a) { float4 v; asm("ld.shared.v4.f32 {%0, %1, %2, %3}, [%4];" : "=f"(v.x), "=f"(v.y), "=f"(v.z), "=f"(v.w) : "r"(a)); return v; }
__device__ __forceinline__ float lds_f_nv(uint32_t a) { float v; asm("ld.shared.f32 %0, [%1];" : "=f"(v) : "r"(a)); return v; }
__device__ __forceinline__ void sts_f(uint32_t a, float v) { asm volatile("st.shared.f32 [%0], %1;" :: "r"(a), "f"(v) : "memory"); }
__device__ __forceinline__ uint4 lds_u4(uint32_t a) { uint4 v; asm volatile("ld.shared.v4.u32 {%0, %1, %2, %3}, [%4];" : "=r"(v.x), "=r"(v.y), "=r"(v.z), "=r"(v.w) : "r"(a)); return v; }
__device__ __forceinline__ float4 lds_f4(uint32_t a) { float4 v; asm volatile("ld.shared.v4.f32 {%0, %1, %2, %3}, [%4];" : "=f"(v.x), "=f"(v.y), "=f"(v.z), "=f"(v.w) : "r"(a)); return v; }
__device__ __forceinline__ uint2 lds_u2(uint32_t a) { uint2 v; asm volatile("ld.shared.v2.u32 {%0, %1}, [%2];" : "=r"(v.x), "=r"(v.y) : "r"(a)); return v; }
__device__ __forceinline__ void sts_u4(uint32_t a, uint4 v) { asm volatile("st.shared.v4.u32 [%0], {%1, %2, %3, %4};" :: "r"(a), "r"(v.x), "r"(v.y), "r"(v.z), "r"(v.w) : "memory"); }
__device__ __forceinline__ void sts_u32(uint32_t a, uint32_t v) { asm volatile("st.shared.u32 [%0], %1;" :: "r"(a), "r"(v) : "memory"); }
__device__ __forceinline__ void sts_u16(uint32_t a, uint16_t v) { asm volatile("st.shared.u16 [%0], %1;" :: "r"(a), "h"(v) : "memory"); }
__device__ __forceinline__ uint32_t lds_u16(uint32_t a) { uint16_t v; asm volatile("ld.shared.u16 %0, [%1];" : "=h"(v) : "r"(a)); return v; }
__device__ __forceinline__ bool elect_one() {
  uint32_t pred;
  asm volatile("{\n.reg .pred p;\nelect.sync _|p, 0xFFFFFFFF;\nselp.b32 %0, 1, 0, p;\n}" : "=r"(pred));
  return pred != 0;
}
__device__ __forceinline__ void cp_async16(uint32_t dst, const void* src) {
  asm volatile("cp.async.cg.shared.global [%0], [%1], 16;" :: "r"(dst), "l"(src) : "memory");
}
__device__ __forceinline__ void named_arrive(int id, int n) { asm volatile("bar.arrive %0, %1;" :: "r"(id), "r"(n) : "memory"); }
__device__ __forceinline__ void sts_f4(uint32_t a, float x, float y, float z, float w) {
  asm volatile("st.shared.v4.f32 [%0], {%1, %2, %3, %4};" :: "r"(a), "f"(x), "f"(y), "f"(z), "f"(w) : "memory");
}
__device__ __forceinline__ void bulk_copy_to_peer(uint32_t rdst, uint32_t src, uint32_t bytes, uint32_t rbar) {
  asm volatile("cp.async.bulk.shared::cluster.shared::cta.mbarrier::complete_tx::bytes [%0], [%1], %2, [%3];"
    :: "r"(rdst), "r"(src), "r"(bytes), "r"(rbar) : "memory");
}
template <int N> __device__ __forceinline__ void acc_fence(float (&acc)[N]) {
#pragma unroll
  for (int i = 0; i < N; i++) asm volatile("" : "+f"(acc[i]) :: "memory");
}
__device__ __forceinline__ void st_cluster_f4(uint32_t raddr, float a, float b, float c, float d) {
  asm volatile("st.shared::cluster.v4.f32 [%0], {%1, %2, %3, %4};" :: "r"(raddr), "f"(a), "f"(b), "f"(c), "f"(d) : "memory");
}
__device__ __forceinline__ void ldsm_x4(uint32_t a, uint32_t& r0, uint32_t& r1, uint32_t& r2, uint32_t& r3) {
  asm volatile("ldmatrix.sync.aligned.m8n8.x4.shared.b16 {%0, %1, %2, %3}, [%4];" : "=r"(r0), "=r"(r1), "=r"(r2), "=r"(r3) : "r"(a));
}
__device__ __forceinline__ void ldsm_x2(uint32_t a, uint32_t& r0, uint32_t& r1) {
  asm volatile("ldmatrix.sync.aligned.m8n8.x2.shared.b16 {%0, %1}, [%2];" : "=r"(r0), "=r"(r1) : "r"(a));
}
__device__ __forceinline__ void ldsm_x1(uint32_t a, uint32_t& r0) {
  asm volatile("ldmatrix.sync.aligned.m8n8.x1.shared.b16 {%0}, [%1];" : "=r"(r0) : "r"(a));
}
__device__ __forceinline__ void ldsm_x4_t(uint32_t a, uint32_t& r0, uint32_t& r1, uint32_t& r2, uint32_t& r3) {
  asm volatile("ldmatrix.sync.aligned.m8n8.x4.trans.shared.b16 {%0, %1, %2, %3}, [%4];" : "=r"(r0), "=r"(r1), "=r"(r2), "=r"(r3) : "r"(a));
}
__device__ __forceinline__ void ldsm_x1_t(uint32_t a, uint32_t& r0) {
  asm volatile("ldmatrix.sync.aligned.m8n8.x1.trans.shared.b16 {%0}, [%1];" : "=r"(r0) : "r"(a));
}
__device__ __forceinline__ void mma_k16(float (&c)[4], uint32_t a0, uint32_t a1, uint32_t a2, uint32_t a3, uint32_t b0, uint32_t b1) {
  asm("mma.sync.aligned.m16n8k16.row.col.f32.bf16.bf16.f32 {%0, %1, %2, %3}, {%4, %5, %6, %7}, {%8, %9}, {%0, %1, %2, %3};"
      : "+f"(c[0]), "+f"(c[1]), "+f"(c[2]), "+f"(c[3]) : "r"(a0), "r"(a1), "r"(a2), "r"(a3), "r"(b0), "r"(b1));
}
__device__ __forceinline__ void mma_k8(float (&c)[4], uint32_t a0, uint32_t a1, uint32_t b0) {
  asm("mma.sync.aligned.m16n8k8.row.col.f32.bf16.bf16.f32 {%0, %1, %2, %3}, {%4, %5}, {%6}, {%0, %1, %2, %3};"
      : "+f"(c[0]), "+f"(c[1]), "+f"(c[2]), "+f"(c[3]) : "r"(a0), "r"(a1), "r"(b0));
}
__device__ __forceinline__ float tanh_fast(float x) { float y; asm("tanh.approx.f32 %0, %1;" : "=f"(y) : "f"(x)); return y; }
__device__ __forceinline__ float rcp_fast(float x) { float y; asm("rcp.approx.ftz.f32 %0, %1;" : "=f"(y) : "f"(x)); return y; }
__device__ __forceinline__ float ex2(float x) { float y; asm("ex2.approx.ftz.f32 %0, %1;" : "=f"(y) : "f"(x)); return y; }
__device__ __forceinline__ float warp_sum(float v) {
#pragma unroll
  for (int o = 16; o > 0; o >>= 1) v += __shfl_xor_sync(0xffffffffu, v, o);
  return v;
}
__device__ __forceinline__ float gelu_half(float hv) {
  const float t = fmaf(hv * hv, 8.f * 0.0356774081f, 2.f * 0.7978845608f);
  return fmaf(hv, tanh_fast(hv * t), hv);
}

__device__ __forceinline__ void cluster_arrive_relaxed() { asm volatile("barrier.cluster.arrive.relaxed.aligned;" ::: "memory"); }
__device__ __forceinline__ void cluster_wait() { asm volatile("barrier.cluster.wait.acquire.aligned;" ::: "memory"); }

template <int OFF, int TOT> __device__ __forceinline__ void wgmma_n128(float (&d)[TOT], uint64_t da, uint64_t db, int sd) {
  asm volatile("{\n.reg .pred p;\nsetp.ne.b32 p, %66, 0;\n"
    "wgmma.mma_async.sync.aligned.m64n128k16.f32.bf16.bf16 "
    "{%0, %1, %2, %3, %4, %5, %6, %7, %8, %9, %10, %11, %12, %13, %14, %15, "
    "%16, %17, %18, %19, %20, %21, %22, %23, %24, %25, %26, %27, %28, %29, %30, %31, "
    "%32, %33, %34, %35, %36, %37, %38, %39, %40, %41, %42, %43, %44, %45, %46, %47, "
    "%48, %49, %50, %51, %52, %53, %54, %55, %56, %57, %58, %59, %60, %61, %62, %63}, "
    "%64, %65, p, 1, 1, 0, 1;\n}\n"
    : "+f"(d[OFF + 0]), "+f"(d[OFF + 1]), "+f"(d[OFF + 2]), "+f"(d[OFF + 3]), "+f"(d[OFF + 4]), "+f"(d[OFF + 5]), "+f"(d[OFF + 6]), "+f"(d[OFF + 7]),
      "+f"(d[OFF + 8]), "+f"(d[OFF + 9]), "+f"(d[OFF + 10]), "+f"(d[OFF + 11]), "+f"(d[OFF + 12]), "+f"(d[OFF + 13]), "+f"(d[OFF + 14]), "+f"(d[OFF + 15]),
      "+f"(d[OFF + 16]), "+f"(d[OFF + 17]), "+f"(d[OFF + 18]), "+f"(d[OFF + 19]), "+f"(d[OFF + 20]), "+f"(d[OFF + 21]), "+f"(d[OFF + 22]), "+f"(d[OFF + 23]),
      "+f"(d[OFF + 24]), "+f"(d[OFF + 25]), "+f"(d[OFF + 26]), "+f"(d[OFF + 27]), "+f"(d[OFF + 28]), "+f"(d[OFF + 29]), "+f"(d[OFF + 30]), "+f"(d[OFF + 31]),
      "+f"(d[OFF + 32]), "+f"(d[OFF + 33]), "+f"(d[OFF + 34]), "+f"(d[OFF + 35]), "+f"(d[OFF + 36]), "+f"(d[OFF + 37]), "+f"(d[OFF + 38]), "+f"(d[OFF + 39]),
      "+f"(d[OFF + 40]), "+f"(d[OFF + 41]), "+f"(d[OFF + 42]), "+f"(d[OFF + 43]), "+f"(d[OFF + 44]), "+f"(d[OFF + 45]), "+f"(d[OFF + 46]), "+f"(d[OFF + 47]),
      "+f"(d[OFF + 48]), "+f"(d[OFF + 49]), "+f"(d[OFF + 50]), "+f"(d[OFF + 51]), "+f"(d[OFF + 52]), "+f"(d[OFF + 53]), "+f"(d[OFF + 54]), "+f"(d[OFF + 55]),
      "+f"(d[OFF + 56]), "+f"(d[OFF + 57]), "+f"(d[OFF + 58]), "+f"(d[OFF + 59]), "+f"(d[OFF + 60]), "+f"(d[OFF + 61]), "+f"(d[OFF + 62]), "+f"(d[OFF + 63])
    : "l"(da), "l"(db), "r"(sd));
}
template <int OFF, int TOT> __device__ __forceinline__ void wgmma_n88(float (&d)[TOT], uint64_t da, uint64_t db, int sd) {
  asm volatile("{\n.reg .pred p;\nsetp.ne.b32 p, %46, 0;\n"
    "wgmma.mma_async.sync.aligned.m64n88k16.f32.bf16.bf16 "
    "{%0, %1, %2, %3, %4, %5, %6, %7, %8, %9, %10, %11, %12, %13, %14, %15, "
    "%16, %17, %18, %19, %20, %21, %22, %23, %24, %25, %26, %27, %28, %29, %30, %31, "
    "%32, %33, %34, %35, %36, %37, %38, %39, %40, %41, %42, %43}, "
    "%44, %45, p, 1, 1, 0, 1;\n}\n"
    : "+f"(d[OFF + 0]), "+f"(d[OFF + 1]), "+f"(d[OFF + 2]), "+f"(d[OFF + 3]), "+f"(d[OFF + 4]), "+f"(d[OFF + 5]), "+f"(d[OFF + 6]), "+f"(d[OFF + 7]),
      "+f"(d[OFF + 8]), "+f"(d[OFF + 9]), "+f"(d[OFF + 10]), "+f"(d[OFF + 11]), "+f"(d[OFF + 12]), "+f"(d[OFF + 13]), "+f"(d[OFF + 14]), "+f"(d[OFF + 15]),
      "+f"(d[OFF + 16]), "+f"(d[OFF + 17]), "+f"(d[OFF + 18]), "+f"(d[OFF + 19]), "+f"(d[OFF + 20]), "+f"(d[OFF + 21]), "+f"(d[OFF + 22]), "+f"(d[OFF + 23]),
      "+f"(d[OFF + 24]), "+f"(d[OFF + 25]), "+f"(d[OFF + 26]), "+f"(d[OFF + 27]), "+f"(d[OFF + 28]), "+f"(d[OFF + 29]), "+f"(d[OFF + 30]), "+f"(d[OFF + 31]),
      "+f"(d[OFF + 32]), "+f"(d[OFF + 33]), "+f"(d[OFF + 34]), "+f"(d[OFF + 35]), "+f"(d[OFF + 36]), "+f"(d[OFF + 37]), "+f"(d[OFF + 38]), "+f"(d[OFF + 39]),
      "+f"(d[OFF + 40]), "+f"(d[OFF + 41]), "+f"(d[OFF + 42]), "+f"(d[OFF + 43])
    : "l"(da), "l"(db), "r"(sd));
}
template <int OFF, int TOT> __device__ __forceinline__ void wgmma_n192(float (&d)[TOT], uint64_t da, uint64_t db, int sd) {
  asm volatile("{\n.reg .pred p;\nsetp.ne.b32 p, %98, 0;\n"
    "wgmma.mma_async.sync.aligned.m64n192k16.f32.bf16.bf16 "
    "{%0, %1, %2, %3, %4, %5, %6, %7, %8, %9, %10, %11, %12, %13, %14, %15, "
    "%16, %17, %18, %19, %20, %21, %22, %23, %24, %25, %26, %27, %28, %29, %30, %31, "
    "%32, %33, %34, %35, %36, %37, %38, %39, %40, %41, %42, %43, %44, %45, %46, %47, "
    "%48, %49, %50, %51, %52, %53, %54, %55, %56, %57, %58, %59, %60, %61, %62, %63, "
    "%64, %65, %66, %67, %68, %69, %70, %71, %72, %73, %74, %75, %76, %77, %78, %79, "
    "%80, %81, %82, %83, %84, %85, %86, %87, %88, %89, %90, %91, %92, %93, %94, %95}, "
    "%96, %97, p, 1, 1, 0, 1;\n}\n"
    : "+f"(d[OFF + 0]), "+f"(d[OFF + 1]), "+f"(d[OFF + 2]), "+f"(d[OFF + 3]), "+f"(d[OFF + 4]), "+f"(d[OFF + 5]), "+f"(d[OFF + 6]), "+f"(d[OFF + 7]),
      "+f"(d[OFF + 8]), "+f"(d[OFF + 9]), "+f"(d[OFF + 10]), "+f"(d[OFF + 11]), "+f"(d[OFF + 12]), "+f"(d[OFF + 13]), "+f"(d[OFF + 14]), "+f"(d[OFF + 15]),
      "+f"(d[OFF + 16]), "+f"(d[OFF + 17]), "+f"(d[OFF + 18]), "+f"(d[OFF + 19]), "+f"(d[OFF + 20]), "+f"(d[OFF + 21]), "+f"(d[OFF + 22]), "+f"(d[OFF + 23]),
      "+f"(d[OFF + 24]), "+f"(d[OFF + 25]), "+f"(d[OFF + 26]), "+f"(d[OFF + 27]), "+f"(d[OFF + 28]), "+f"(d[OFF + 29]), "+f"(d[OFF + 30]), "+f"(d[OFF + 31]),
      "+f"(d[OFF + 32]), "+f"(d[OFF + 33]), "+f"(d[OFF + 34]), "+f"(d[OFF + 35]), "+f"(d[OFF + 36]), "+f"(d[OFF + 37]), "+f"(d[OFF + 38]), "+f"(d[OFF + 39]),
      "+f"(d[OFF + 40]), "+f"(d[OFF + 41]), "+f"(d[OFF + 42]), "+f"(d[OFF + 43]), "+f"(d[OFF + 44]), "+f"(d[OFF + 45]), "+f"(d[OFF + 46]), "+f"(d[OFF + 47]),
      "+f"(d[OFF + 48]), "+f"(d[OFF + 49]), "+f"(d[OFF + 50]), "+f"(d[OFF + 51]), "+f"(d[OFF + 52]), "+f"(d[OFF + 53]), "+f"(d[OFF + 54]), "+f"(d[OFF + 55]),
      "+f"(d[OFF + 56]), "+f"(d[OFF + 57]), "+f"(d[OFF + 58]), "+f"(d[OFF + 59]), "+f"(d[OFF + 60]), "+f"(d[OFF + 61]), "+f"(d[OFF + 62]), "+f"(d[OFF + 63]),
      "+f"(d[OFF + 64]), "+f"(d[OFF + 65]), "+f"(d[OFF + 66]), "+f"(d[OFF + 67]), "+f"(d[OFF + 68]), "+f"(d[OFF + 69]), "+f"(d[OFF + 70]), "+f"(d[OFF + 71]),
      "+f"(d[OFF + 72]), "+f"(d[OFF + 73]), "+f"(d[OFF + 74]), "+f"(d[OFF + 75]), "+f"(d[OFF + 76]), "+f"(d[OFF + 77]), "+f"(d[OFF + 78]), "+f"(d[OFF + 79]),
      "+f"(d[OFF + 80]), "+f"(d[OFF + 81]), "+f"(d[OFF + 82]), "+f"(d[OFF + 83]), "+f"(d[OFF + 84]), "+f"(d[OFF + 85]), "+f"(d[OFF + 86]), "+f"(d[OFF + 87]),
      "+f"(d[OFF + 88]), "+f"(d[OFF + 89]), "+f"(d[OFF + 90]), "+f"(d[OFF + 91]), "+f"(d[OFF + 92]), "+f"(d[OFF + 93]), "+f"(d[OFF + 94]), "+f"(d[OFF + 95])
    : "l"(da), "l"(db), "r"(sd));
}
template <int OFF, int TOT> __device__ __forceinline__ void wgmma_n48(float (&d)[TOT], uint64_t da, uint64_t db, int sd) {
  asm volatile("{\n.reg .pred p;\nsetp.ne.b32 p, %26, 0;\n"
    "wgmma.mma_async.sync.aligned.m64n48k16.f32.bf16.bf16 "
    "{%0, %1, %2, %3, %4, %5, %6, %7, %8, %9, %10, %11, %12, %13, %14, %15, "
    "%16, %17, %18, %19, %20, %21, %22, %23}, "
    "%24, %25, p, 1, 1, 0, 1;\n}\n"
    : "+f"(d[OFF + 0]), "+f"(d[OFF + 1]), "+f"(d[OFF + 2]), "+f"(d[OFF + 3]), "+f"(d[OFF + 4]), "+f"(d[OFF + 5]), "+f"(d[OFF + 6]), "+f"(d[OFF + 7]),
      "+f"(d[OFF + 8]), "+f"(d[OFF + 9]), "+f"(d[OFF + 10]), "+f"(d[OFF + 11]), "+f"(d[OFF + 12]), "+f"(d[OFF + 13]), "+f"(d[OFF + 14]), "+f"(d[OFF + 15]),
      "+f"(d[OFF + 16]), "+f"(d[OFF + 17]), "+f"(d[OFF + 18]), "+f"(d[OFF + 19]), "+f"(d[OFF + 20]), "+f"(d[OFF + 21]), "+f"(d[OFF + 22]), "+f"(d[OFF + 23])
    : "l"(da), "l"(db), "r"(sd));
}
template <int OFF, int TOT> __device__ __forceinline__ void wgmma_n160(float (&d)[TOT], uint64_t da, uint64_t db, int sd) {
  asm volatile("{\n.reg .pred p;\nsetp.ne.b32 p, %82, 0;\n"
    "wgmma.mma_async.sync.aligned.m64n160k16.f32.bf16.bf16 "
    "{%0, %1, %2, %3, %4, %5, %6, %7, %8, %9, %10, %11, %12, %13, %14, %15, "
    "%16, %17, %18, %19, %20, %21, %22, %23, %24, %25, %26, %27, %28, %29, %30, %31, "
    "%32, %33, %34, %35, %36, %37, %38, %39, %40, %41, %42, %43, %44, %45, %46, %47, "
    "%48, %49, %50, %51, %52, %53, %54, %55, %56, %57, %58, %59, %60, %61, %62, %63, "
    "%64, %65, %66, %67, %68, %69, %70, %71, %72, %73, %74, %75, %76, %77, %78, %79}, "
    "%80, %81, p, 1, 1, 0, 1;\n}\n"
    : "+f"(d[OFF + 0]), "+f"(d[OFF + 1]), "+f"(d[OFF + 2]), "+f"(d[OFF + 3]), "+f"(d[OFF + 4]), "+f"(d[OFF + 5]), "+f"(d[OFF + 6]), "+f"(d[OFF + 7]),
      "+f"(d[OFF + 8]), "+f"(d[OFF + 9]), "+f"(d[OFF + 10]), "+f"(d[OFF + 11]), "+f"(d[OFF + 12]), "+f"(d[OFF + 13]), "+f"(d[OFF + 14]), "+f"(d[OFF + 15]),
      "+f"(d[OFF + 16]), "+f"(d[OFF + 17]), "+f"(d[OFF + 18]), "+f"(d[OFF + 19]), "+f"(d[OFF + 20]), "+f"(d[OFF + 21]), "+f"(d[OFF + 22]), "+f"(d[OFF + 23]),
      "+f"(d[OFF + 24]), "+f"(d[OFF + 25]), "+f"(d[OFF + 26]), "+f"(d[OFF + 27]), "+f"(d[OFF + 28]), "+f"(d[OFF + 29]), "+f"(d[OFF + 30]), "+f"(d[OFF + 31]),
      "+f"(d[OFF + 32]), "+f"(d[OFF + 33]), "+f"(d[OFF + 34]), "+f"(d[OFF + 35]), "+f"(d[OFF + 36]), "+f"(d[OFF + 37]), "+f"(d[OFF + 38]), "+f"(d[OFF + 39]),
      "+f"(d[OFF + 40]), "+f"(d[OFF + 41]), "+f"(d[OFF + 42]), "+f"(d[OFF + 43]), "+f"(d[OFF + 44]), "+f"(d[OFF + 45]), "+f"(d[OFF + 46]), "+f"(d[OFF + 47]),
      "+f"(d[OFF + 48]), "+f"(d[OFF + 49]), "+f"(d[OFF + 50]), "+f"(d[OFF + 51]), "+f"(d[OFF + 52]), "+f"(d[OFF + 53]), "+f"(d[OFF + 54]), "+f"(d[OFF + 55]),
      "+f"(d[OFF + 56]), "+f"(d[OFF + 57]), "+f"(d[OFF + 58]), "+f"(d[OFF + 59]), "+f"(d[OFF + 60]), "+f"(d[OFF + 61]), "+f"(d[OFF + 62]), "+f"(d[OFF + 63]),
      "+f"(d[OFF + 64]), "+f"(d[OFF + 65]), "+f"(d[OFF + 66]), "+f"(d[OFF + 67]), "+f"(d[OFF + 68]), "+f"(d[OFF + 69]), "+f"(d[OFF + 70]), "+f"(d[OFF + 71]),
      "+f"(d[OFF + 72]), "+f"(d[OFF + 73]), "+f"(d[OFF + 74]), "+f"(d[OFF + 75]), "+f"(d[OFF + 76]), "+f"(d[OFF + 77]), "+f"(d[OFF + 78]), "+f"(d[OFF + 79])
    : "l"(da), "l"(db), "r"(sd));
}

template <int N> __device__ __forceinline__ void mma_step(float (&acc)[N / 2], uint32_t a_lo, uint32_t b_lo,
                                                          int accumulate, bool release, uint32_t release_bar, uint32_t release_peer, int lane) {
  wgmma_fence();
#pragma unroll
  for (int kk = 0; kk < 4; kk++) {
    const uint64_t da = desc(a_lo + kk * 2, DESC_HI_128);
    const int sd = kk == 0 ? accumulate : 1;
    if constexpr (N == N3) {
      wgmma_n160<0>(acc, da, desc(b_lo + (((kk >> 1) * 12288 + (kk & 1) * 2048) >> 4), DESC_HI_128), sd);
    } else {
      const uint32_t bk = b_lo + (((kk >> 1) * 16384 + (kk & 1) * 2048) >> 4);
      if constexpr (N == N1) {
        wgmma_n128<0>(acc, da, desc(bk, DESC_HI_128), sd);
        wgmma_n88<64>(acc, da, desc(bk + (8192 >> 4), DESC_HI_128), sd);
      } else {
        const uint32_t br = b_lo + (((kk >> 1) * 16384 + 12288 + (kk & 1) * 512) >> 4) - ((4096 >> 4) << 16) + ((1024 >> 4) << 16);
        wgmma_n192<0>(acc, da, desc(bk, DESC_HI_128), sd);
        wgmma_n48<96>(acc, da, desc(br, DESC_HI_32), sd);
      }
    }
    if (kk == 0) {
      wgmma_commit();
      wgmma_wait<1>();
      if (release && lane == 0) { mbar_arrive(release_bar); mbar_arrive_remote(release_peer); }
    }
  }
  wgmma_commit();
}

template <int N> __device__ __forceinline__ void mainloop1(float (&acc)[N / 2], uint32_t base, int g0, int rank, int wg, int lane, int trace_id) {
  const uint32_t bars = base + OFF_BAR;
  const uint32_t peer_empty = mapa(bars + 8 * BAR_P1_EMPTY, 1 - rank);
  const uint32_t a_lo = desc_lo(base + OFF_A + wg * 8192, 16), b_lo = desc_lo(base + OFF_B, 4096);
  int s = g0 % 3, ph = (g0 / 3) & 1, prev = 0;
#pragma unroll 1
  for (int k = 0; k < 10; k++) {
    mbar_wait(bars + 8 * (BAR_P1_FULL + s), ph);
    if (threadIdx.x == 0) TR(32 + g0 + k);
    if (N == N1 && k == GATE_STEP && threadIdx.x == 0) mbar_arrive(bars + 8 * BAR_GATE);
    mma_step<N>(acc, a_lo + s * (A_SLOT >> 4), b_lo + s * (4 * B_BLK >> 4), k > 0, k > 0,
                bars + 8 * (BAR_P1_EMPTY + prev), peer_empty + 8 * prev, lane);
    prev = s;
    if (++s == 3) { s = 0; ph ^= 1; }
  }
  wgmma_wait<0>();
  acc_fence(acc);
  if (lane == 0) { mbar_arrive(bars + 8 * (BAR_P1_EMPTY + prev)); mbar_arrive_remote(peer_empty + 8 * prev); }
}

__device__ __forceinline__ void gelu_epilogue(const float (&acc)[N1 / 2], uint32_t base, int wg, int warp, int lane) {
  const int row0 = wg * 64 + warp * 16;
  const float r0 = lds_f(base + OFF_RH + 4 * (row0 + (lane >> 2))), r1 = lds_f(base + OFF_RH + 4 * (row0 + 8 + (lane >> 2)));
  const float m0 = -r0 * lds_f(base + OFF_MEAN + 4 * (row0 + (lane >> 2)));
  const float m1 = -r1 * lds_f(base + OFF_MEAN + 4 * (row0 + 8 + (lane >> 2)));
  const uint32_t cba = base + OFF_CB + 16 * (lane & 3);
  const int mi = lane >> 3, r8 = lane & 7;
  const int lrow = row0 + (mi & 1) * 8 + r8;
  const uint32_t dst = base + OFF_STG + lrow * 128;
  const uint32_t dstl = base + OFF_HL + lrow * 48 + (mi >> 1) * 16;
  float4 c[2][2];
  c[0][0] = lds_f4(cba); c[0][1] = lds_f4(cba + 64);
#pragma unroll
  for (int jp = 0; jp < 14; jp++) {
    const int cur = jp & 1;
    if (jp < 13) { c[cur ^ 1][0] = lds_f4(cba + 128 * (jp + 1)); if (2 * (jp + 1) + 1 < 27) c[cur ^ 1][1] = lds_f4(cba + 128 * (jp + 1) + 64); }
    uint32_t pk[4];
#pragma unroll
    for (int h = 0; h < 2; h++) {
      const int j = 2 * jp + h;
      if (j < 27) {
        const float4 cc = c[cur][h];
        const float v0 = gelu_half(fmaf(acc[4 * j + 0], r0, fmaf(m0, cc.x, cc.z))), v1 = gelu_half(fmaf(acc[4 * j + 1], r0, fmaf(m0, cc.y, cc.w)));
        const float v2 = gelu_half(fmaf(acc[4 * j + 2], r1, fmaf(m1, cc.x, cc.z))), v3 = gelu_half(fmaf(acc[4 * j + 3], r1, fmaf(m1, cc.y, cc.w)));
        pk[2 * h] = pack_bf16(v0, v1);
        pk[2 * h + 1] = pack_bf16(v2, v3);
      }
    }
    if (jp < 12) stsm_x4(dst + (jp >> 2) * 16384 + ((((2 * jp & 7) + (mi >> 1)) ^ r8) << 4), pk[0], pk[1], pk[2], pk[3]);
    else if (jp == 12) stsm_x4(dstl, pk[0], pk[1], pk[2], pk[3]);
    else stsm_x2(dstl - (mi >> 1) * 16 + 32, pk[0], pk[1]);
  }
}

__device__ __forceinline__ void dump_qkv(const float (&acc)[N2 / 2], uint32_t base_in, int wg, int warp, int lane) {
  const uint32_t base = launder(base_in);
  const int row0 = wg * 64 + warp * 16;
  const float m0 = lds_f_nv(base + OFF_MEAN + 4 * (row0 + (lane >> 2)));
  const float m1 = lds_f_nv(base + OFF_MEAN + 4 * (row0 + 8 + (lane >> 2)));
  const uint32_t csa = base + OFF_CS2 + 8 * (lane & 3);
  const int mi = lane >> 3;
  const uint32_t dst = base + OFF_STG + (row0 + (mi & 1) * 8 + (lane & 7)) * QP + (mi >> 1) * 16;
#pragma unroll
  for (int j = 0; j < 30; j += 2) {
    const int off = j < 24 ? (j >> 3) * 160 + (j & 7) * 16 : ((j - 24) >> 1) * 160 + 128;
    const float2 c0 = lds_f2_nv(csa + 32 * j), c1 = lds_f2_nv(csa + 32 * (j + 1));
    stsm_x4(dst + off,
            pack_bf16(fmaf(-m0, c0.x, acc[4 * j + 0]), fmaf(-m0, c0.y, acc[4 * j + 1])),
            pack_bf16(fmaf(-m1, c0.x, acc[4 * j + 2]), fmaf(-m1, c0.y, acc[4 * j + 3])),
            pack_bf16(fmaf(-m0, c1.x, acc[4 * j + 4]), fmaf(-m0, c1.y, acc[4 * j + 5])),
            pack_bf16(fmaf(-m1, c1.x, acc[4 * j + 6]), fmaf(-m1, c1.y, acc[4 * j + 7])));
  }
}

template <int KS> __device__ __forceinline__ void final_epilogue(const float (&acc)[80], const Params& p, uint32_t base, int b, int mt, int nt,
                                                                 int wg, int warp, int lane, int trace_id) {
  constexpr int KEEP = KS * 40, SEND = (1 - KS) * 40;
  const uint32_t bars = base + OFF_BAR;
  const int w8 = wg * 4 + warp;
  const uint32_t tag = lds_u32(base + OFF_TAG);
  const uint32_t sendbuf = base + OFF_SEND + w8 * 2560;
  mbar_wait(bars + 8 * BAR_XT, 0);
#pragma unroll
  for (int j = 0; j < 5; j++) {
    uint4 u;
    u.x = pack_bf16(acc[SEND + 8 * j], acc[SEND + 8 * j + 1]); u.y = pack_bf16(acc[SEND + 8 * j + 2], acc[SEND + 8 * j + 3]);
    u.z = pack_bf16(acc[SEND + 8 * j + 4], acc[SEND + 8 * j + 5]); u.w = pack_bf16(acc[SEND + 8 * j + 6], acc[SEND + 8 * j + 7]);
    sts_u4(sendbuf + j * 512 + lane * 16, u);
  }
  fence_async_smem();
  __syncwarp();
  if (elect_one()) { bulk_store(g_part + (b * 8 + w8) * 160, sendbuf, 2560); bulk_commit(); }
  __syncwarp();
  cluster_arrive_relaxed();
  const int mi = lane >> 3;
  const int lrow = w8 * 16 + (mi & 1) * 8 + (lane & 7);
  auto tile_off = [&](int j) -> uint32_t {
    return KS == 0 ? lrow * 160 + j * 32 + (mi >> 1) * 16
                   : j < 3 ? lrow * 96 + j * 32 + (mi >> 1) * 16 : 12288 + lrow * 64 + (j - 3) * 32 + (mi >> 1) * 16;
  };
  const uint32_t ba = base + OFF_B2 + 8 * (lane & 3);
  float v[40];
#pragma unroll
  for (int j = 0; j < 5; j++) {
    uint32_t x0, x1, x2, x3;
    ldsm_x4(base + OFF_XT + tile_off(j), x0, x1, x2, x3);
    const float2 b0 = lds_f2(ba + 64 * j), b1 = lds_f2(ba + 64 * j + 32);
    v[8 * j] = acc[KEEP + 8 * j] + b0.x + bf_lo(x0); v[8 * j + 1] = acc[KEEP + 8 * j + 1] + b0.y + bf_hi(x0);
    v[8 * j + 2] = acc[KEEP + 8 * j + 2] + b0.x + bf_lo(x1); v[8 * j + 3] = acc[KEEP + 8 * j + 3] + b0.y + bf_hi(x1);
    v[8 * j + 4] = acc[KEEP + 8 * j + 4] + b1.x + bf_lo(x2); v[8 * j + 5] = acc[KEEP + 8 * j + 5] + b1.y + bf_hi(x2);
    v[8 * j + 6] = acc[KEEP + 8 * j + 6] + b1.x + bf_lo(x3); v[8 * j + 7] = acc[KEEP + 8 * j + 7] + b1.y + bf_hi(x3);
  }
  if (elect_one()) {
    bulk_wait();
    st_tagged(&g_pflag[b * 8 + w8], 0u, tag);
  }
  __syncwarp();
  if (threadIdx.x == 0) TR(6);
  if (lane == 0) { ld_tagged_fast(&g_pflag[(b ^ 8) * 8 + w8], tag); asm volatile("fence.acq_rel.cta;" ::: "memory"); }
  __syncwarp();
  uint4 o[5];
  const uint4* inbox = g_part + ((b ^ 8) * 8 + w8) * 160 + lane;
#pragma unroll
  for (int j = 0; j < 5; j++) o[j] = __ldcg(inbox + j * 32);
  if (threadIdx.x == 0) TR(7);
#pragma unroll
  for (int j = 0; j < 5; j++)
    stsm_x4(base + OFF_OUT + tile_off(j),
            pack_bf16(v[8 * j] + bf_lo(o[j].x), v[8 * j + 1] + bf_hi(o[j].x)), pack_bf16(v[8 * j + 2] + bf_lo(o[j].y), v[8 * j + 3] + bf_hi(o[j].y)),
            pack_bf16(v[8 * j + 4] + bf_lo(o[j].z), v[8 * j + 5] + bf_hi(o[j].z)), pack_bf16(v[8 * j + 6] + bf_lo(o[j].w), v[8 * j + 7] + bf_hi(o[j].w)));
  fence_async_smem();
  named_bar(3, 256);
  if (w8 == 0 && elect_one()) {
    if (KS == 0) tma_store_2d(&p.tm_o80, base + OFF_OUT, 128 * nt, mt * 128);
    else {
      tma_store_2d(&p.tm_o48, base + OFF_OUT, 128 * nt + 80, mt * 128);
      tma_store_2d(&p.tm_o32, base + OFF_OUT + 12288, 512 + 32 * nt, mt * 128);
    }
    bulk_commit();
    bulk_wait_read();
  }
  __syncwarp();
  if (threadIdx.x == 0) TR(27);
  cluster_wait();
}

__device__ __forceinline__ void attn_pair(uint32_t base, int w16, int lane, bool arrive = true) {
  const int r0 = (w16 >> 1) * 16, hp = w16 & 1;
  const int g = lane >> 2, q = lane & 3, mi = lane >> 3, r8 = lane & 7;
  const uint32_t stg = base + OFF_STG + hp * 80;
  const uint32_t qrow = stg + (r0 + (mi & 1) * 8 + r8) * QP;
  const uint32_t k0 = stg + max(r0 - 7 + r8, 0) * QP, k1 = stg + (r0 + 1 + r8) * QP, k2 = stg + min(r0 + 9 + r8, 127) * QP;
  const uint32_t pA = mi < 3 ? k0 + mi * 16 : k1, pB = mi < 2 ? k1 + 16 + mi * 16 : k2 + (mi - 2) * 16, pC = k2 + 32;
  uint32_t qa[2][4], qb[2][2], kf[2][9], vf[2][9];
#pragma unroll
  for (int h = 0; h < 2; h++) {
    ldsm_x4(qrow + (mi >> 1) * 16 + 32 * h, qa[h][0], qa[h][1], qa[h][2], qa[h][3]);
    ldsm_x2(qrow + 32 + 32 * h, qb[h][0], qb[h][1]);
    ldsm_x4(pA + 160 + 32 * h, kf[h][0], kf[h][1], kf[h][2], kf[h][3]);
    ldsm_x4(pB + 160 + 32 * h, kf[h][4], kf[h][5], kf[h][6], kf[h][7]);
    ldsm_x1(pC + 160 + 32 * h, kf[h][8]);
  }
  const bool d0 = 2 * q >= g, d1 = 2 * q + 1 >= g;
  const int key0 = r0 - 7 + 2 * q + (d0 ? 0 : 8), key1 = r0 - 6 + 2 * q + (d1 ? 0 : 8);
  const uint32_t r1a = base + OFF_R1;
  const float rk0 = lds_f(r1a + 4 * max(key0, 0)), rk1 = lds_f(r1a + 4 * max(key1, 0));
  const float rk2 = lds_f(r1a + 4 * (key0 + 8)), rk3 = lds_f(r1a + 4 * (key1 + 8));
  constexpr float SC = 0.22360679775f * 1.44269504089f;
  const float rq0 = SC * lds_f(r1a + 4 * (r0 + g)), rq1 = SC * lds_f(r1a + 4 * (r0 + g + 8));
  const float f0 = rq0 * rk0, f1 = rq0 * rk1, f2 = rq1 * rk2, f3 = rq1 * rk3;
  if (q >= 2) { qb[0][0] = 0; qb[0][1] = 0; } else { qa[1][0] = 0; qa[1][1] = 0; }
  float c[2][3][4];
#pragma unroll
  for (int h = 0; h < 2; h++)
#pragma unroll
    for (int t = 0; t < 3; t++) {
#pragma unroll
      for (int e = 0; e < 4; e++) c[h][t][e] = 0.f;
      mma_k16(c[h][t], qa[h][0], qa[h][1], qa[h][2], qa[h][3], kf[h][3 * t], kf[h][3 * t + 1]);
    }
#pragma unroll
  for (int h = 0; h < 2; h++)
#pragma unroll
    for (int t = 0; t < 3; t++) mma_k8(c[h][t], qb[h][0], qb[h][1], kf[h][3 * t + 2]);
#pragma unroll
  for (int h = 0; h < 2; h++) {
    ldsm_x4_t(pA + 320 + 32 * h, vf[h][0], vf[h][1], vf[h][2], vf[h][3]);
    ldsm_x4_t(pB + 320 + 32 * h, vf[h][4], vf[h][5], vf[h][6], vf[h][7]);
    ldsm_x1_t(pC + 320 + 32 * h, vf[h][8]);
  }
  float s[2][4];
#pragma unroll
  for (int h = 0; h < 2; h++) {
    s[h][0] = key0 >= 0 ? (d0 ? c[h][0][0] : c[h][1][0]) * f0 : -INFINITY;
    s[h][1] = key1 >= 0 ? (d1 ? c[h][0][1] : c[h][1][1]) * f1 : -INFINITY;
    s[h][2] = (d0 ? c[h][1][2] : c[h][2][2]) * f2;
    s[h][3] = (d1 ? c[h][1][3] : c[h][2][3]) * f3;
  }
  float m[2][2];
#pragma unroll
  for (int h = 0; h < 2; h++) { m[h][0] = fmaxf(s[h][0], s[h][1]); m[h][1] = fmaxf(s[h][2], s[h][3]); }
#pragma unroll
  for (int o = 1; o <= 2; o <<= 1)
#pragma unroll
    for (int h = 0; h < 2; h++) {
      m[h][0] = fmaxf(m[h][0], __shfl_xor_sync(0xffffffffu, m[h][0], o));
      m[h][1] = fmaxf(m[h][1], __shfl_xor_sync(0xffffffffu, m[h][1], o));
    }
#pragma unroll
  for (int h = 0; h < 2; h++) {
    s[h][0] = ex2(s[h][0] - m[h][0]); s[h][1] = ex2(s[h][1] - m[h][0]);
    s[h][2] = ex2(s[h][2] - m[h][1]); s[h][3] = ex2(s[h][3] - m[h][1]);
    m[h][0] = s[h][0] + s[h][1]; m[h][1] = s[h][2] + s[h][3];
  }
#pragma unroll
  for (int o = 1; o <= 2; o <<= 1)
#pragma unroll
    for (int h = 0; h < 2; h++) {
      m[h][0] += __shfl_xor_sync(0xffffffffu, m[h][0], o);
      m[h][1] += __shfl_xor_sync(0xffffffffu, m[h][1], o);
    }
  const uint32_t orow = base + OFF_O + (r0 + g) * 160 + hp * 80 + 4 * q;
#pragma unroll
  for (int h = 0; h < 2; h++) {
    const float i0 = rcp_fast(m[h][0]), i1 = rcp_fast(m[h][1]);
    const float p0 = s[h][0] * i0 * rk0, p1 = s[h][1] * i0 * rk1, p2 = s[h][2] * i1 * rk2, p3 = s[h][3] * i1 * rk3;
    const uint32_t pa0 = pack_bf16(d0 ? p0 : 0.f, d1 ? p1 : 0.f);
    const uint32_t pa2 = pack_bf16(d0 ? 0.f : p0, d1 ? 0.f : p1);
    const uint32_t pa3 = pack_bf16(d0 ? p2 : 0.f, d1 ? p3 : 0.f);
    const uint32_t pb1 = pack_bf16(d0 ? 0.f : p2, d1 ? 0.f : p3);
#pragma unroll
    for (int t = 0; t < 3; t++) {
#pragma unroll
      for (int e = 0; e < 4; e++) c[h][t][e] = 0.f;
      mma_k16(c[h][t], pa0, 0u, pa2, pa3, vf[h][t], vf[h][3 + t]);
      mma_k8(c[h][t], 0u, pb1, vf[h][6 + t]);
    }
  }
#pragma unroll
  for (int h = 0; h < 2; h++)
#pragma unroll
    for (int t = 0; t < 3; t++) {
      const bool ok = t == 1 || (t == 0 ? (h == 0 || q >= 2) : (h == 1 || q < 2));
      if (ok) {
        sts_u32(orow + 32 * h + 16 * t, pack_bf16(c[h][t][0], c[h][t][1]));
        sts_u32(orow + 8 * 160 + 32 * h + 16 * t, pack_bf16(c[h][t][2], c[h][t][3]));
      }
    }
  fence_async_smem();
  __syncwarp();
  if (lane == 0 && arrive) mbar_arrive(base + OFF_BAR + 8 * BAR_ATT);
}

__global__ void __cluster_dims__(2, 1, 1) __launch_bounds__(512, 1)
fused_block_kernel(const __grid_constant__ Params p) {
  extern __shared__ __align__(1024) uint8_t smem_raw[];
  const uint32_t base = smem_u32(smem_raw);
  const uint32_t bars = base + OFF_BAR;
  const int rank = blockIdx.x & 1;
  const int warp_id = __shfl_sync(0xffffffffu, threadIdx.x >> 5, 0), lane = threadIdx.x & 31;
  const int wg = warp_id >> 2, warp = warp_id & 3;

  int grp, idx;
  {
    uint32_t smid, nsmid;
    asm("mov.u32 %0, %%smid;" : "=r"(smid));
    asm("mov.u32 %0, %%nsmid;" : "=r"(nsmid));
    const int t = nsmid == NGRID ? smid >> 1 : blockIdx.x >> 1;
    if (t < 32) { grp = t & 7; idx = t >> 3; }
    else if (t < 60) { grp = 1 + (t - 32) % 7; idx = 4 + (t - 32) / 7; }
    else if (t < 62) return;
    else { grp = 0; idx = 4 + (t - 62); }
  }
  const int b = (grp * 8 + idx) * 2 + rank;
  const int trace_id = b; (void)trace_id;
  const int tb = 2 * (grp & 3) + (idx >> 2), nt1 = 4 * (grp >> 2) + (idx & 3);
  const int mt2 = 2 * grp + rank, nt2 = idx & 3, ks = idx >> 2;
  const int nh = ks == 0 ? 14 : 13, h0 = ks == 0 ? 0 : 14, o0 = ks * 5;
  const int nsteps2 = nh + 5;

  if (wg < 2) {
    reg_alloc<152>();
    named_bar(1, 288);
    cluster_arrive_relaxed();
    cluster_wait();
    {
      float acc[N1 / 2];
      mainloop1<N1>(acc, base, 0, rank, wg, lane, trace_id);
      if (threadIdx.x == 0) TR(8);
      mbar_wait(bars + 8 * BAR_MISC, 0);
      if (threadIdx.x == 0) mbar_arrive(bars + 8 * BAR_R1END);
      gelu_epilogue(acc, base, wg, warp, lane);
      fence_async_smem();
      __syncwarp();
      if (lane == 0) mbar_arrive(bars + 8 * BAR_STG_FULL);
      if (threadIdx.x == 0) TR(9);
    }
    {
      float acc[N2 / 2];
      mainloop1<N2>(acc, base, 10, rank, wg, lane, trace_id);
      if (threadIdx.x == 0) TR(10);
      mbar_wait(bars + 8 * BAR_STG_FREE, 0);
      dump_qkv(acc, base, wg, warp, lane);
      __syncwarp();
      if (lane == 0) mbar_arrive(bars + 8 * BAR_STG_FULL);
      if (threadIdx.x == 0) TR(11);
    }
    mbar_wait(bars + 8 * BAR_STG_FULL, 1);
    if (threadIdx.x == 0) TR(54);
    attn_pair(base, warp_id, lane);
    if (threadIdx.x == 0) TR(52);
    if (threadIdx.x == 96) TR(55);
    if (threadIdx.x == 160) TR(56);
    if (threadIdx.x == 224) TR(57);
    mbar_wait(bars + 8 * BAR_ATT, 0);
    mbar_wait(bars + 8 * BAR_GO, 0);
    if (threadIdx.x == 0) TR(53);
    {
      float acc[N3 / 2];
      int prev = 0;
      const uint32_t peer_empty2 = mapa(bars + 8 * BAR_P2_EMPTY, 1 - rank);
      const uint32_t a_lo = desc_lo(base + OFF_A + wg * 8192, 16), b_lo = desc_lo(base + OFF_B, 4096);
#pragma unroll 1
      for (int i = 0; i < nsteps2; i++) {
        const int q = i & 3;
        mbar_wait(bars + 8 * (BAR_P2_FULL + q), (i >> 2) & 1);
        if (threadIdx.x == 0 && i == 0) TR(12);
        if (threadIdx.x == 0) TR(64 + i);
        const int sl = (q + 3) & 3;
        mma_step<N3>(acc, a_lo + sl * (A_SLOT >> 4), b_lo + sl * (3 * B_BLK >> 4), i > 0, i > 0 && i + 3 < nsteps2,
                     bars + 8 * (BAR_P2_EMPTY + prev), peer_empty2 + 8 * prev, lane);
        prev = q;
      }
      wgmma_wait<0>();
      acc_fence(acc);
      if (threadIdx.x == 0) TR(13);
      if (threadIdx.x == 0) {
        uint32_t peer_id;
        asm volatile("ld.shared::cluster.u32 %0, [%1];" : "=r"(peer_id) : "r"(mapa(base + OFF_ID, 1 - rank)));
        if (peer_id != (uint32_t)(grp * 8 + idx)) asm volatile("trap;");
      }
      if (ks == 0) final_epilogue<0>(acc, p, base, b, mt2, nt2, wg, warp, lane, trace_id);
      else final_epilogue<1>(acc, p, base, b, mt2, nt2, wg, warp, lane, trace_id);
      if (threadIdx.x == 0) { TR(14); atomicAdd(&g_cnt[CNT_EXIT], 1u); TR(15); }
    }
  } else {
    reg_dealloc<104>();
    if (warp_id == 8) {
      auto issue_p1 = [&](int g, int s) {
        const uint32_t full = bars + 8 * (BAR_P1_FULL + s);
        const uint32_t bdst = base + OFF_B + s * 4 * B_BLK + rank * 16384;
        const int k = g < 10 ? g : g - 10;
        mbar_expect_tx(full, g < 10 ? A_SLOT + 4 * B_BLK : A_SLOT + 2 * 15360);
        tma_3d(base + OFF_A + s * A_SLOT, &p.tm_x, k * 64, rank, tb * 128, full);
        if (g < 10) {
          tma_3d_mc(bdst, &p.tm_w1a, 0, k * 64 + rank * 32, 3 * nt1, full);
          tma_3d_mc(bdst + 3 * 4096, &p.tm_w1b, 0, k * 64 + rank * 32, nt1, full);
        } else {
          tma_4d_mc(bdst, &p.tm_qm, 0, k * 64 + rank * 32, nt1, 0, full);
          tma_4d_mc(bdst + 12288, &p.tm_qr, 64, k * 64 + rank * 32, nt1, 0, full);
        }
      };
      uint32_t epoch = 0;
      auto issue_p2 = [&](int i) {
        const int q = i & 3;
        if (i == 0) mbar_wait(bars + 8 * (BAR_P1_EMPTY + 2), 1);
        else if (i == 1) mbar_wait(bars + 8 * (BAR_P1_EMPTY + 0), 0);
        else if (i == 2) mbar_wait(bars + 8 * (BAR_P1_EMPTY + 1), 0);
        else if (i == 3) mbar_wait(bars + 8 * BAR_OFREE, 0);
        else if (i >= 4) mbar_wait(bars + 8 * (BAR_P2_EMPTY + q), ((i >> 2) & 1) ^ 1);
        TR(88 + i);
        const uint32_t full = bars + 8 * (BAR_P2_FULL + q);
        const uint32_t bb = base + OFF_B + ((q + 3) & 3) * 3 * B_BLK + rank * 12288;
        mbar_expect_tx(full, A_SLOT + 3 * B_BLK);
        const bool is_h = i < nh;
        const int krow = is_h ? (h0 + i) * 64 : (o0 + i - nh) * 64;
        tma_3d_mc(bb, is_h ? &p.tm_w2a : &p.tm_woa, 0, krow + rank * 32, 2 * nt2, full);
        tma_3d_mc(bb + 8192, is_h ? &p.tm_w2b : &p.tm_wob, 0, krow + rank * 32, nt2, full);
        if (i == 0) { wait_counter(&g_cnt[CNT_H + 32 * (mt2 >> 1)], (epoch + 1) * 16); fence_async_global(); TR(2); }
        if (i == nh) { TR(3); wait_counter(&g_cnt[CNT_O + 32 * (mt2 >> 1)], (epoch + 1) * 16); fence_async_global(); TR(4); }
        tma_2d(base + OFF_A + ((q + 3) & 3) * A_SLOT, &p.tm_act, is_h ? krow : FF + krow, mt2 * 128, full);
        TR(108 + i);
      };
      if (lane == 0) {
#pragma unroll
        for (int i = 0; i < BAR_COUNT; i++)
          mbar_init(bars + 8 * i, (i >= BAR_P1_EMPTY && i < BAR_P2_FULL) || (i >= BAR_P2_EMPTY && i < BAR_STG_FULL) || i == BAR_ATT ? 16
                                  : i == BAR_STG_FULL ? 8 : i == BAR_OFREE ? 2 : 1);
        asm volatile("fence.mbarrier_init.release.cluster;" ::: "memory");
        if (base & 1023) asm volatile("trap;");
        asm volatile("st.shared.u32 [%0], %1;" :: "r"(base + OFF_ID), "r"(grp * 8 + idx) : "memory");
      }
      __syncwarp();
      named_arrive(1, 288);
      named_arrive(4, 256);
      cluster_arrive_relaxed();
      cluster_wait();
      if (elect_one()) {
#pragma unroll 1
        for (int g = 0; g < 3; g++) { issue_p1(g, g); if (g == 0) TR(61); }
        TR(1);
#pragma unroll 1
        for (int k = 3; k < 3 + TPF_K; k++) {
          tma_prefetch_3d(&p.tm_x, k * 64, rank, tb * 128);
          tma_prefetch_3d(&p.tm_w1a, 0, k * 64 + rank * 32, 3 * nt1);
          tma_prefetch_3d(&p.tm_w1b, 0, k * 64 + rank * 32, nt1);
        }
        epoch = ld_relaxed(&g_cnt[CNT_EXIT]) / NCTA;
        prefetch_tmap(&p.tm_qm); prefetch_tmap(&p.tm_qr); prefetch_tmap(&p.tm_act); prefetch_tmap(&p.tm_w2a); prefetch_tmap(&p.tm_w2b);
        prefetch_tmap(&p.tm_woa); prefetch_tmap(&p.tm_wob);
        int s = 0, ph = 0;
#pragma unroll 1
        for (int g = 3; g < 20; g++) {
          mbar_wait(bars + 8 * (BAR_P1_EMPTY + s), ph);
          issue_p1(g, s);
          if (g == 11) {
            l2_prefetch(reinterpret_cast<const uint8_t*>(p.w2) + b * 17280, 17280);
            l2_prefetch(reinterpret_cast<const uint8_t*>(p.wo) + b * 6400, 6400);
          }
          if (++s == 3) { s = 0; ph ^= 1; }
        }
        wait_counter(&g_cnt[CNT_START], (epoch + 1) * NCTA);
#pragma unroll 1
        for (int i = 0; i < PRE_P2; i++) issue_p2(i);
      }
      __syncwarp();
      mbar_wait(bars + 8 * BAR_STG_FULL, 1);
      if (lane == 0) TR(58);
      attn_pair(base, 8, lane);
      if (lane == 0) TR(59);
      if (elect_one()) {
        mbar_wait(bars + 8 * BAR_ATT, 0);
        tma_store_3d(&p.tm_ost, base + OFF_O + 7 * 160, FF + nt1 * 80, rank, tb * 128 + 7);
        bulk_commit();
        bulk_wait_read();
        mbar_arrive(bars + 8 * BAR_OFREE);
        mbar_arrive_remote(mapa(bars + 8 * BAR_OFREE, 1 - rank));
#pragma unroll 1
        for (int i = PRE_P2; i < nsteps2; i++) {
          issue_p2(i);
          if (i == 4) { bulk_wait(); mbar_arrive(bars + 8 * BAR_OMAIN); }
        }
      }
      __syncwarp();
    } else {
      const int t = threadIdx.x - 288, sw = warp_id - 9;
      cluster_arrive_relaxed();
      if (t == 32) { prefetch_tmap(&p.tm_x); prefetch_tmap(&p.tm_w1a); prefetch_tmap(&p.tm_w1b); }
      const uint32_t epoch = ld_relaxed(&g_cnt[CNT_EXIT]) / NCTA;
      const uint32_t tag = epoch + 1;
      auto align_group = [&](const unsigned long long* stamps, uint32_t delay_ns, int bar) {
        const uint32_t ts = ld_tagged(&stamps[grp * 16 + (lane & 15)], tag);
        const uint32_t now = gtime_lo();
        int32_t d = (int32_t)(ts - now);
#pragma unroll
        for (int o = 8; o > 0; o >>= 1) d = max(d, __shfl_xor_sync(0xffffffffu, d, o));
        const uint32_t go = now + d + delay_ns;
        while ((int32_t)(gtime_lo() - go) < 0) __nanosleep(20);
        if (lane == 0) mbar_arrive(bars + 8 * bar);
        __syncwarp();
      };
      const long long t_start = clock64();
      named_bar(4, 256);
      const bool isw1 = b < 54;
      const int col0 = (isw1 ? b : b - 54) * 32;
      cluster_wait();
      if (sw == 6) {
        while (clock64() - t_start < PF_DELAY) {}
      }
      if (sw != 6) while (clock64() - t_start < SIDE_DELAY) {}
      if (sw == 6 && b < 114) {
        while (clock64() - t_start < SIDE_DELAY) {}
        if (elect_one()) mbar_expect_tx(bars + 8 * BAR_CS, 40960);
#pragma unroll 1
        for (int i = 0; i < 640 / CS_ROWS; i++) {
          if (i > 0) __nanosleep(CS_GAP);
          if (elect_one()) tma_2d(base + OFF_STG + i * (CS_ROWS * 64), isw1 ? &p.tm_c1 : &p.tm_c2, col0, i * CS_ROWS, bars + 8 * BAR_CS);
          __syncwarp();
        }
      }

      uint4 xv[3][3];
#pragma unroll
      for (int r = 0; r < 3; r++) {
        const uint4* src = reinterpret_cast<const uint4*>(p.x + (size_t)(b * 16 + min(sw + 7 * r, 15)) * DM);
        xv[r][0] = __ldg(src + lane); xv[r][1] = __ldg(src + 32 + lane);
        xv[r][2] = __ldg(src + 64 + (lane & 15));
      }
      {
        float sh[3], a[3], q2[3];
#pragma unroll
        for (int r = 0; r < 3; r++) {
          sh[r] = __shfl_sync(0xffffffffu, bf_lo(xv[r][0].x), 0);
          float a0 = 0.f, a1 = 0.f, b0 = 0.f, b1 = 0.f;
#pragma unroll
          for (int c = 0; c < 3; c++) {
            const uint32_t u[4] = {xv[r][c].x, xv[r][c].y, xv[r][c].z, xv[r][c].w};
            const float live = (c < 2 || lane < 16) ? 1.f : 0.f;
#pragma unroll
            for (int e = 0; e < 4; e++) {
              float lo = bf_lo(u[e]) - sh[r], hi = bf_hi(u[e]) - sh[r];
              if (c == 2) { lo *= live; hi *= live; }
              a0 += lo; a1 += hi; b0 = fmaf(lo, lo, b0); b1 = fmaf(hi, hi, b1);
            }
          }
          a[r] = a0 + a1; q2[r] = b0 + b1;
        }
#pragma unroll
        for (int o = 16; o > 0; o >>= 1)
#pragma unroll
          for (int r = 0; r < 3; r++) { a[r] += __shfl_xor_sync(0xffffffffu, a[r], o); q2[r] += __shfl_xor_sync(0xffffffffu, q2[r], o); }
        if (lane < 3 && sw + 7 * lane < 16) {
          const float sa = lane == 0 ? a[0] : lane == 1 ? a[1] : a[2];
          const float sq = lane == 0 ? q2[0] : lane == 1 ? q2[1] : q2[2];
          const float s0 = lane == 0 ? sh[0] : lane == 1 ? sh[1] : sh[2];
          const float md = sa * (1.f / DM);
          const float var = fmaxf(sq * (1.f / DM) - md * md, 0.f);
          const float r1 = rsqrtf(var + 1e-5f);
          const float r2 = rsqrtf(var * r1 * r1 + 1e-5f);
          const int row = b * 16 + sw + 7 * lane;
          st_tagged(&g_stat[row], __float_as_uint(s0 + md), tag);
          st_tagged(&g_stat[S + row], __float_as_uint(r1), tag);
          st_tagged(&g_stat[2 * S + row], __float_as_uint(0.5f * r1 * r2), tag);
        }
      }
      __syncwarp();
      if (t == 0) TR(28);
      if (b < 114) {
        mbar_wait(bars + 8 * BAR_CS, 0);
        if (t == 0) TR(5);
        const uint32_t sa = base + OFF_STG + t * 16;
        uint4 v[12];
#pragma unroll
        for (int i = 0; i < 12; i++) v[i] = lds_u4(sa + ((i < 11 || t < 96) ? i : 0) * (NSIDE * 16));
        float a[8];
#pragma unroll
        for (int e = 0; e < 8; e++) a[e] = 0.f;
#pragma unroll
        for (int i = 0; i < 12; i++) {
          if (i < 11 || t < 96) {
            a[0] += bf_lo(v[i].x); a[1] += bf_hi(v[i].x); a[2] += bf_lo(v[i].y); a[3] += bf_hi(v[i].y);
            a[4] += bf_lo(v[i].z); a[5] += bf_hi(v[i].z); a[6] += bf_lo(v[i].w); a[7] += bf_hi(v[i].w);
          }
        }
#pragma unroll
        for (int o = 4; o <= 16; o <<= 1)
#pragma unroll
          for (int e = 0; e < 8; e++) a[e] += __shfl_xor_sync(0xffffffffu, a[e], o);
        const uint32_t red = base + OFF_CS2;
        if (lane < 4) {
          sts_f4(red + 4 * (sw * 32 + lane * 8), a[0], a[1], a[2], a[3]);
          sts_f4(red + 4 * (sw * 32 + lane * 8 + 4), a[4], a[5], a[6], a[7]);
        }
        named_bar(2, NSIDE);
        if (t < 32) {
          float sum = 0.f;
#pragma unroll
          for (int w7 = 0; w7 < 7; w7++) sum += lds_f(red + 4 * (w7 * 32 + t));
          st_tagged(g_cs + (isw1 ? 0 : FF) + col0 + t, __float_as_uint(sum), tag);
        }
      }
      if (t == 0) TR(29);
      named_bar(2, NSIDE);
      if (t == 0) asm volatile("red.relaxed.gpu.global.add.u32 [%0], 1;" :: "l"(&g_cnt[CNT_START]) : "memory");
      const int tok0 = tb * 256 + rank;
      mbar_wait(bars + 8 * BAR_GATE, 0);
      {
        const int tk = tok0 + 2 * (t & 127);
        const int c = t < 192 ? 192 * nt1 + t : 1536 + 24 * nt1 + min(t - 192, 23);
        unsigned long long w0 = ld_word(&g_stat[tk]), w1 = ld_word(&g_stat[S + tk]), w2 = ld_word(&g_stat[2 * S + tk]), w3 = ld_word(&g_cs[c]);
        const float bias = 0.5f * __bfloat162float(p.b1[c]);
        if ((w0 >> 32) != tag) w0 = ld_tagged(&g_stat[tk], tag);
        if ((w1 >> 32) != tag) w1 = ld_tagged(&g_stat[S + tk], tag);
        if ((w2 >> 32) != tag) w2 = ld_tagged(&g_stat[2 * S + tk], tag);
        if ((w3 >> 32) != tag) w3 = ld_tagged(&g_cs[c], tag);
        if (t < 128) {
          sts_u32(base + OFF_MEAN + 4 * t, (uint32_t)w0); sts_u32(base + OFF_R1 + 4 * t, (uint32_t)w1); sts_u32(base + OFF_RH + 4 * t, (uint32_t)w2);
        }
        if (t < N1) {
          sts_f(base + OFF_CB + 16 * (t >> 1) + 8 + 4 * (t & 1), bias);
          sts_u32(base + OFF_CB + 16 * (t >> 1) + 4 * (t & 1), (uint32_t)w3);
        }
      }
      if (t == 0) sts_u32(base + OFF_TAG, tag);
      named_bar(2, NSIDE);
      if (t == 0) { mbar_arrive(bars + 8 * BAR_MISC); TR(17); }

      if (sw == 0) {
        mbar_wait(bars + 8 * BAR_STG_FULL, 0);
        if (t == 0) TR(19);
#pragma unroll 1
        for (int i = 0; i < 3 * (128 / H_ROWS); i++) {
          if (elect_one()) tma_store_4d(&p.tm_hst, base + OFF_STG + (i % 3) * 16384 + (i / 3) * (H_ROWS * 128), 0, rank, tb * 128 + (i / 3) * H_ROWS, 3 * nt1 + i % 3);
          __nanosleep(H_GAP);
        }
        if (elect_one()) { tma_store_4d(&p.tm_hsl, base + OFF_HL, 0, rank, tb * 128, nt1); bulk_commit(); bulk_wait_read(); }
        __syncwarp();
      }
      for (int n = t; n < N2; n += NSIDE) {
        const int part = n < 192 ? n >> 6 : (n - 192) >> 4, c = n < 192 ? n & 63 : 64 + ((n - 192) & 15);
        sts_u32(base + OFF_CS2 + 4 * n, ld_tagged(&g_cs[FF + part * DM + nt1 * 80 + c], tag));
      }
      named_bar(2, NSIDE);
      if (sw == 0 && elect_one()) {
        mbar_arrive(bars + 8 * BAR_STG_FREE);
        TR(20);
        bulk_wait();
        red_after_bulk(&g_cnt[CNT_H + 32 * tb]);
        TR(21);
      }
      __syncwarp();

      const int me = (tb * 2 + rank) * 8 + nt1;
      const int hw = t & 7, hi = (t >> 3) % 7, hh = (t >> 3) / 7, kr = hi - 7 + hw;
      const bool kvalid = tb > 0 || kr >= 0;
      const float rkey = kvalid ? __uint_as_float(ld_tagged(&g_stat[S + tok0 + 2 * kr], tag)) : 0.f;
      mbar_wait(bars + 8 * BAR_STG_FULL, 1);
      if (t == 0) TR(22);
      if (t == 32) st_tagged(&g_sync[128 + b], gtime_lo(), tag);
      if (tb < 7) {
        uint32_t hv[3];
#pragma unroll
        for (int i = 0; i < 3; i++) { const int c = min(t + i * NSIDE, 559); hv[i] = lds_u32(base + OFF_STG + (121 + c / 80) * QP + 160 + (c % 80) * 4); }
#pragma unroll
        for (int i = 0; i < 3; i++) if (t + i * NSIDE < 560) st_tagged(&g_halo[me * 560 + t + i * NSIDE], hv[i], tag);
      }
      attn_pair(base, warp_id, lane);
      if (t == 0) TR(23);
      if (sw == 1) align_group(g_sync + 128, GO_DELAY_NS, BAR_GO);
      if (tb > 0) {
        if (t == 0) ld_tagged(&g_halo[(me - 16) * 560 + 559], tag);
        named_bar(2, NSIDE);
        unsigned long long hw3[3];
#pragma unroll
        for (int i = 0; i < 3; i++) hw3[i] = ld_word(&g_halo[(me - 16) * 560 + min(t + i * NSIDE, 559)]);
#pragma unroll
        for (int i = 0; i < 3; i++) {
          const int c = t + i * NSIDE;
          if (c < 560) sts_u32(base + OFF_HALO + c * 4, (hw3[i] >> 32) == tag ? (uint32_t)hw3[i] : ld_tagged(&g_halo[(me - 16) * 560 + c], tag));
        }
      } else {
        for (int c = t; c < 560; c += NSIDE) sts_u32(base + OFF_HALO + c * 4, 0u);
      }
      named_bar(2, NSIDE);
      if (t == 0) TR(24);
      {
        const uint32_t qa = base + OFF_STG + hi * QP + hh * 40;
        const uint32_t ka = kr >= 0 ? base + OFF_STG + kr * QP + 160 + hh * 40 : base + OFF_HALO + (kr + 7) * 320 + hh * 40;
        float s0 = 0.f, s1 = 0.f;
#pragma unroll
        for (int c = 0; c < 5; c++) {
          const uint2 a = lds_u2(qa + 8 * c), k = lds_u2(ka + 8 * c);
          s0 = fmaf(bf_lo(a.x), bf_lo(k.x), s0); s1 = fmaf(bf_hi(a.x), bf_hi(k.x), s1);
          s0 = fmaf(bf_lo(a.y), bf_lo(k.y), s0); s1 = fmaf(bf_hi(a.y), bf_hi(k.y), s1);
        }
        float sc = kvalid ? (s0 + s1) * (0.22360679775f * 1.44269504089f) * lds_f(base + OFF_R1 + 4 * hi) * rkey : -INFINITY;
        float mx = sc;
#pragma unroll
        for (int o = 1; o < 8; o <<= 1) mx = fmaxf(mx, __shfl_xor_sync(0xffffffffu, mx, o));
        sc = ex2(sc - mx);
        float sum = sc;
#pragma unroll
        for (int o = 1; o < 8; o <<= 1) sum += __shfl_xor_sync(0xffffffffu, sum, o);
        sc = __bfloat162float(__float2bfloat16(sc * rcp_fast(sum) * rkey));
        float o0 = 0.f, o1 = 0.f, o2 = 0.f, o3 = 0.f;
#pragma unroll
        for (int j = 0; j < 8; j++) {
          const float pj = __shfl_sync(0xffffffffu, sc, (lane & 24) + j);
          const int vr = hi - 7 + j;
          const uint32_t va = (vr >= 0 ? base + OFF_STG + vr * QP + 320 : base + OFF_HALO + (vr + 7) * 320 + 160) + hh * 40 + 4 * hw;
          const uint32_t u = lds_u32(va);
          o0 = fmaf(pj, bf_lo(u), o0); o1 = fmaf(pj, bf_hi(u), o1);
          if (hw < 2) { const uint32_t u2 = lds_u32(va + 32); o2 = fmaf(pj, bf_lo(u2), o2); o3 = fmaf(pj, bf_hi(u2), o3); }
        }
        const uint32_t od = base + OFF_O7 + hi * 160 + hh * 40 + 4 * hw;
        sts_u32(od, pack_bf16(o0, o1));
        if (hw < 2) sts_u32(od + 32, pack_bf16(o2, o3));
        fence_async_smem();
      }
      named_bar(2, NSIDE);
      if (sw == 6 && elect_one()) {
        tma_store_3d(&p.tm_os7, base + OFF_O7, FF + nt1 * 80, rank, tb * 128);
        bulk_commit();
        bulk_wait();
        mbar_wait(bars + 8 * BAR_OMAIN, 0);
        red_after_bulk(&g_cnt[CNT_O + 32 * tb]);
        TR(26);
      }
      __syncwarp();
      {
        uint4 xr[6];
#pragma unroll
        for (int i = 0; i < 6; i++) {
          const int c = min(t + i * NSIDE, 1279), r = (c * 6554) >> 16, cc = c - r * 10, jj = ks * 10 + cc;
          xr[i] = __ldg(reinterpret_cast<const uint4*>(p.x + (size_t)(mt2 * 128 + r) * DM + (jj < 16 ? 128 * nt2 + 8 * jj : 512 + 32 * nt2 + 8 * (jj - 16))));
        }
#pragma unroll
        for (int i = 0; i < 6; i++) {
          const int c = t + i * NSIDE, r = (c * 6554) >> 16, cc = c - r * 10;
          if (c < 1280) sts_u4(base + OFF_XT + (ks == 0 ? r * 160 + cc * 16 : cc < 6 ? r * 96 + cc * 16 : 12288 + r * 64 + (cc - 6) * 16), xr[i]);
        }
      }
      if (t >= 64 && t < 144) {
        const int n = t - 64, jj = ks * 10 + (n >> 3);
        const int col = (jj < 16 ? 128 * nt2 + 8 * jj : 512 + 32 * nt2 + 8 * (jj - 16)) + (n & 7);
        sts_f(base + OFF_B2 + 4 * n, __bfloat162float(p.b2[col]));
      }
      named_bar(2, NSIDE);
      if (t == 0) mbar_arrive(bars + 8 * BAR_XT);
    }
  }
}

typedef CUresult (*EncodeFn)(CUtensorMap*, CUtensorMapDataType, cuuint32_t, void*, const cuuint64_t*, const cuuint64_t*,
                             const cuuint32_t*, const cuuint32_t*, CUtensorMapInterleave, CUtensorMapSwizzle,
                             CUtensorMapL2promotion, CUtensorMapFloatOOBfill);

#define PROMO_DEFAULT CU_TENSOR_MAP_L2_PROMOTION_L2_128B
#define PROMO_Q CU_TENSOR_MAP_L2_PROMOTION_L2_128B
static void make_map(EncodeFn fn, CUtensorMap* m, const void* ptr, int rank, const cuuint64_t* dims, const cuuint64_t* strides,
                     const cuuint32_t* box, CUtensorMapSwizzle swz, CUtensorMapL2promotion promo = PROMO_DEFAULT) {
  cuuint32_t es[4] = {1, 1, 1, 1};
  fn(m, CU_TENSOR_MAP_DATA_TYPE_BFLOAT16, rank, const_cast<void*>(ptr), dims, strides, box, es, CU_TENSOR_MAP_INTERLEAVE_NONE,
     swz, promo, CU_TENSOR_MAP_FLOAT_OOB_FILL_NONE);
}

extern "C" void kernel_launch(void* const* d_in, const int* in_sizes, int n_in, void* d_out, int out_size) {
  (void)in_sizes; (void)n_in; (void)out_size;
  const bf16* x = (const bf16*)d_in[0];
  const bf16* wqkv = (const bf16*)d_in[1];
  const bf16* wo = (const bf16*)d_in[2];
  const bf16* w1 = (const bf16*)d_in[4];
  const bf16* b1 = (const bf16*)d_in[5];
  const bf16* w2 = (const bf16*)d_in[6];
  const bf16* b2 = (const bf16*)d_in[7];

  static EncodeFn fn = nullptr;
  static void* act = nullptr;
  if (!fn) {
    void* f = nullptr;
    cudaDriverEntryPointQueryResult qr;
    cudaGetDriverEntryPoint("cuTensorMapEncodeTiled", &f, cudaEnableDefault, &qr);
    fn = (EncodeFn)f;
    cudaGetSymbolAddress(&act, g_act);
    cudaFuncSetAttribute(fused_block_kernel, cudaFuncAttributeMaxDynamicSharedMemorySize, SMEM_LAUNCH);
  }
  const CUtensorMapSwizzle SW128 = CU_TENSOR_MAP_SWIZZLE_128B, SW32 = CU_TENSOR_MAP_SWIZZLE_32B, SWN = CU_TENSOR_MAP_SWIZZLE_NONE;
  Params p;
  { cuuint64_t d[3] = {DM, 2, S / 2}, s[2] = {DM * 2, DM * 4}; cuuint32_t bx[3] = {64, 1, 128}; make_map(fn, &p.tm_x, x, 3, d, s, bx, SW128); }
  { cuuint64_t d[3] = {64, DM, 27}, s[2] = {FF * 2, 128}; cuuint32_t bx[3] = {64, 32, 3}; make_map(fn, &p.tm_w1a, w1, 3, d, s, bx, SW128); }
  { cuuint64_t d[3] = {24, DM, 8}, s[2] = {FF * 2, 48}; cuuint32_t bx[3] = {64, 32, 1}; make_map(fn, &p.tm_w1b, w1 + 1536, 3, d, s, bx, SW128); }
  { cuuint64_t d[4] = {80, DM, 8, 3}, s[3] = {NQKV * 2, 160, DM * 2}; cuuint32_t bx[4] = {64, 32, 1, 3}; make_map(fn, &p.tm_qm, wqkv, 4, d, s, bx, SW128, PROMO_Q); }
  { cuuint64_t d[4] = {80, DM, 8, 3}, s[3] = {NQKV * 2, 160, DM * 2}; cuuint32_t bx[4] = {16, 32, 1, 3}; make_map(fn, &p.tm_qr, wqkv, 4, d, s, bx, SW32, PROMO_Q); }
  { cuuint64_t d[2] = {KACT, S}, s[1] = {KACT * 2}; cuuint32_t bx[2] = {64, 128}; make_map(fn, &p.tm_act, act, 2, d, s, bx, SW128); }
  { cuuint64_t d[3] = {64, FF, 10}, s[2] = {DM * 2, 128}; cuuint32_t bx[3] = {64, 32, 2}; make_map(fn, &p.tm_w2a, w2, 3, d, s, bx, SW128); }
  { cuuint64_t d[3] = {32, FF, 4}, s[2] = {DM * 2, 64}; cuuint32_t bx[3] = {64, 32, 1}; make_map(fn, &p.tm_w2b, w2 + 512, 3, d, s, bx, SW128); }
  { cuuint64_t d[3] = {64, DM, 10}, s[2] = {DM * 2, 128}; cuuint32_t bx[3] = {64, 32, 2}; make_map(fn, &p.tm_woa, wo, 3, d, s, bx, SW128); }
  { cuuint64_t d[3] = {32, DM, 4}, s[2] = {DM * 2, 64}; cuuint32_t bx[3] = {64, 32, 1}; make_map(fn, &p.tm_wob, wo + 512, 3, d, s, bx, SW128); }
  { cuuint64_t d[2] = {FF, DM}, s[1] = {FF * 2}; cuuint32_t bx[2] = {32, CS_ROWS}; make_map(fn, &p.tm_c1, w1, 2, d, s, bx, SWN); }
  { cuuint64_t d[2] = {NQKV, DM}, s[1] = {NQKV * 2}; cuuint32_t bx[2] = {32, CS_ROWS}; make_map(fn, &p.tm_c2, wqkv, 2, d, s, bx, SWN); }
  for (int i = 0; i < 3; i++) {
    cuuint64_t d[2] = {DM, S}, s[1] = {DM * 2}; cuuint32_t bx[2] = {i == 0 ? 80u : i == 1 ? 48u : 32u, 128};
    make_map(fn, i == 0 ? &p.tm_o80 : i == 1 ? &p.tm_o48 : &p.tm_o32, d_out, 2, d, s, bx, SWN);
  }
  { cuuint64_t d[4] = {64, 2, S / 2, 27}, s[3] = {KACT * 2, KACT * 4, 128}; cuuint32_t bx[4] = {64, 1, H_ROWS, 1}; make_map(fn, &p.tm_hst, act, 4, d, s, bx, SW128); }
  { cuuint64_t d[4] = {24, 2, S / 2, 8}, s[3] = {KACT * 2, KACT * 4, 48}; cuuint32_t bx[4] = {24, 1, 128, 1}; make_map(fn, &p.tm_hsl, (bf16*)act + 1536, 4, d, s, bx, SWN); }
  { cuuint64_t d[3] = {KACT, 2, S / 2}, s[2] = {KACT * 2, KACT * 4}; cuuint32_t bx[3] = {80, 1, 7}; make_map(fn, &p.tm_os7, act, 3, d, s, bx, SWN); }
  { cuuint64_t d[3] = {KACT, 2, S / 2}, s[2] = {KACT * 2, KACT * 4}; cuuint32_t bx[3] = {80, 1, 121}; make_map(fn, &p.tm_ost, act, 3, d, s, bx, SWN); }
  p.x = x; p.w1 = w1; p.wqkv = wqkv; p.w2 = w2; p.wo = wo; p.b1 = b1; p.b2 = b2; p.out = (bf16*)d_out;
  fused_block_kernel<<<NGRID, 512, SMEM_LAUNCH, cudaStreamPerThread>>>(p);
}
```
